```python
import torch

def _softmax(x, axis=-1):
    return torch.softmax(x, dim=axis)

def _gelu(x):
    return torch.nn.functional.gelu(x, approximate='tanh')

def _silu(x):
    return torch.nn.functional.silu(x)

def _sigmoid(x):
    return torch.sigmoid(x)

def _layernorm(x, axis=-1, eps=1e-05):
    m = x.mean(dim=axis, keepdim=True)
    v = x.var(dim=axis, keepdim=True, unbiased=False)
    return (x - m) / torch.sqrt(v + eps)

def _scatter_add(tgt, idx, src, axis=0):
    return tgt.clone().index_add_(axis, idx, src)

def _segment_sum(src, seg, n):
    out = torch.zeros((n,) + src.shape[1:], dtype=src.dtype)
    return out.index_add_(0, seg, src)

def _pad(x, pw):
    flat = tuple((v for pair in reversed(pw) for v in pair))
    return torch.nn.functional.pad(x, flat)
kernel_name = 'standalone__video_video_swin__vision'

def setup_inputs():

    _w = lambda a: (lambda t: t.to(torch.bfloat16) if t.is_floating_point() else t)(torch.as_tensor(a))
    T = 4
    H = W = 224 // 7 * 7
    C, win = (192, 7)
    return {'x': _w((lambda *s: torch.randn(*s, dtype=torch.bfloat16) * 0.1)(1, T, H, W, C)), 'wqkv_t': _w((lambda *s: torch.randn(*s, dtype=torch.bfloat16) * 0.1)(C, 3 * C)), 'wo_t': _w((lambda *s: torch.randn(*s, dtype=torch.bfloat16) * 0.1)(C, C)), 'wqkv_s': _w((lambda *s: torch.randn(*s, dtype=torch.bfloat16) * 0.1)(C, 3 * C)), 'wo_s': _w((lambda *s: torch.randn(*s, dtype=torch.bfloat16) * 0.05)(C, C))}

def reference(x, wqkv_t, wo_t, wqkv_s, wo_s):
    B, T, H, W, C = x.shape
    win = 7
    scale = C ** (-0.5)
    h = _layernorm(x, axis=-1)
    ht = (lambda x, *d: x.permute(*d))(h, 0, 2, 3, 1, 4).reshape(B * H * W, T, C)
    qkv = ht @ wqkv_t
    q, k, v = (qkv[..., :C].clone(), qkv[..., C:2 * C].clone(), qkv[..., 2 * C:].clone())
    p = _softmax(torch.einsum('btc,bsc->bts', q, k) * scale, axis=-1)
    ot = torch.einsum('bts,bsc->btc', p, v) @ wo_t
    ot = (lambda x, *d: x.permute(*d))(ot.reshape(B, H, W, T, C), 0, 3, 1, 2, 4)
    x = x + ot
    h = _layernorm(x, axis=-1)
    nh, nw = (H // win, W // win)
    hs = h.reshape(B * T, nh, win, nw, win, C)
    hw = (lambda x, *d: x.permute(*d))(hs, 0, 1, 3, 2, 4, 5).reshape(B * T * nh * nw, win * win, C)
    qkv = hw @ wqkv_s
    q, k, v = (qkv[..., :C].clone(), qkv[..., C:2 * C].clone(), qkv[..., 2 * C:].clone())
    p = _softmax(torch.einsum('bqc,bkc->bqk', q, k) * scale, axis=-1)
    os = torch.einsum('bqk,bkc->bqc', p, v) @ wo_s
    os = (lambda x, *d: x.permute(*d))(os.reshape(B * T, nh, nw, win, win, C), 0, 1, 3, 2, 4, 5)
    os = os.reshape(B, T, H, W, C)
    return x + os
```

```cpp
#include <cuda_runtime.h>
#include <cuda_bf16.h>
#include <cuda.h>
#include <stdint.h>

namespace {

constexpr int CH = 192;
constexpr int TT = 4, HH = 224, WW = 224;
constexpr int NTOK = TT * HH * WW;
constexpr int PANEL_X = 64 * 128;
constexpr int SLOT_BYTES = 3 * PANEL_X;
constexpr int PANEL_W = 192 * 128;
constexpr int WMAT_BYTES = 3 * PANEL_W;
constexpr int NWG = 3;
constexpr int SMEM_W0 = 0;
constexpr int SMEM_W1 = WMAT_BYTES;
constexpr int SMEM_SLOT = 2 * WMAT_BYTES;
constexpr int SMEM_MISC = SMEM_SLOT + NWG * SLOT_BYTES;
constexpr int SMEM_RBUF = SMEM_MISC + 64;
constexpr int SMEM_TOTAL = SMEM_RBUF + NWG * 64 * 4;

constexpr int NTILE_A = HH * (WW / 16);
constexpr int NUNIT_B = 32 * 32 * 4;

__device__ __nv_bfloat16 g_x1[(size_t)NTOK * CH];
__device__ __align__(1024) __nv_bfloat16 g_w[4][CH * CH];

__device__ __forceinline__ uint32_t smem_u32(const void* p) { return (uint32_t)__cvta_generic_to_shared(p); }

__device__ __forceinline__ void mbar_init(uint32_t bar, uint32_t count) {
  asm volatile("mbarrier.init.shared::cta.b64 [%0], %1;" :: "r"(bar), "r"(count));
}
__device__ __forceinline__ void mbar_expect_tx(uint32_t bar, uint32_t bytes) {
  asm volatile("mbarrier.arrive.expect_tx.shared::cta.b64 _, [%0], %1;" :: "r"(bar), "r"(bytes) : "memory");
}
__device__ __forceinline__ void mbar_wait(uint32_t bar, uint32_t parity) {
  asm volatile(
    "{\n.reg .pred p;\n"
    "WAIT_%=:\n"
    "mbarrier.try_wait.parity.shared::cta.b64 p, [%0], %1;\n"
    "@p bra DONE_%=;\n"
    "bra WAIT_%=;\n"
    "DONE_%=:\n}\n" :: "r"(bar), "r"(parity) : "memory");
}
__device__ __forceinline__ void tma_load_4d(uint32_t dst, const CUtensorMap* map, int c0, int c1, int c2, int c3, uint32_t bar) {
  asm volatile("cp.async.bulk.tensor.4d.shared::cluster.global.tile.mbarrier::complete_tx::bytes [%0], [%1, {%2, %3, %4, %5}], [%6];"
    :: "r"(dst), "l"(map), "r"(c0), "r"(c1), "r"(c2), "r"(c3), "r"(bar) : "memory");
}
__device__ __forceinline__ void tma_store_4d(const CUtensorMap* map, uint32_t src, int c0, int c1, int c2, int c3) {
  asm volatile("cp.async.bulk.tensor.4d.global.shared::cta.tile.bulk_group [%0, {%1, %2, %3, %4}], [%5];"
    :: "l"(map), "r"(c0), "r"(c1), "r"(c2), "r"(c3), "r"(src) : "memory");
}
__device__ __forceinline__ void bulk_load(uint32_t dst, const void* src, uint32_t bytes, uint32_t bar) {
  asm volatile("cp.async.bulk.shared::cluster.global.mbarrier::complete_tx::bytes [%0], [%1], %2, [%3];"
    :: "r"(dst), "l"(src), "r"(bytes), "r"(bar) : "memory");
}
__device__ __forceinline__ void bulk_commit() { asm volatile("cp.async.bulk.commit_group;" ::: "memory"); }
__device__ __forceinline__ void bulk_wait_read0() { asm volatile("cp.async.bulk.wait_group.read 0;" ::: "memory"); }
__device__ __forceinline__ void bulk_wait0() { asm volatile("cp.async.bulk.wait_group 0;" ::: "memory"); }
__device__ __forceinline__ void fence_proxy_async() { asm volatile("fence.proxy.async.shared::cta;" ::: "memory"); }
__device__ __forceinline__ void wg_bar(int id) { asm volatile("bar.sync %0, 128;" :: "r"(id) : "memory"); }
__device__ __forceinline__ void wgmma_fence() { asm volatile("wgmma.fence.sync.aligned;" ::: "memory"); }
__device__ __forceinline__ void wgmma_commit() { asm volatile("wgmma.commit_group.sync.aligned;" ::: "memory"); }
__device__ __forceinline__ void wgmma_wait0() { asm volatile("wgmma.wait_group.sync.aligned 0;" ::: "memory"); }

__device__ __forceinline__ uint64_t make_desc(uint32_t saddr, uint32_t lbo, uint32_t sbo) {
  return (uint64_t)((saddr & 0x3FFFF) >> 4) | ((uint64_t)((lbo & 0x3FFFF) >> 4) << 16) |
         ((uint64_t)((sbo & 0x3FFFF) >> 4) << 32) | ((uint64_t)1 << 62);
}
__device__ __forceinline__ uint32_t pack_bf16(float lo, float hi) {
  uint32_t r; asm("cvt.rn.bf16x2.f32 %0, %1, %2;" : "=r"(r) : "f"(hi), "f"(lo)); return r;
}
__device__ __forceinline__ float bf_lo(uint32_t u) { return __uint_as_float(u << 16); }
__device__ __forceinline__ float bf_hi(uint32_t u) { return __uint_as_float(u & 0xffff0000u); }
__device__ __forceinline__ void ldsm_x4(uint32_t addr, uint32_t& r0, uint32_t& r1, uint32_t& r2, uint32_t& r3) {
  asm volatile("ldmatrix.sync.aligned.m8n8.x4.shared.b16 {%0,%1,%2,%3}, [%4];"
    : "=r"(r0), "=r"(r1), "=r"(r2), "=r"(r3) : "r"(addr) : "memory");
}
__device__ __forceinline__ void ldsm_x4_t(uint32_t addr, uint32_t& r0, uint32_t& r1, uint32_t& r2, uint32_t& r3) {
  asm volatile("ldmatrix.sync.aligned.m8n8.x4.trans.shared.b16 {%0,%1,%2,%3}, [%4];"
    : "=r"(r0), "=r"(r1), "=r"(r2), "=r"(r3) : "r"(addr) : "memory");
}
__device__ __forceinline__ void stsm_x4(uint32_t addr, uint32_t r0, uint32_t r1, uint32_t r2, uint32_t r3) {
  asm volatile("stmatrix.sync.aligned.m8n8.x4.shared.b16 [%0], {%1,%2,%3,%4};"
    :: "r"(addr), "r"(r0), "r"(r1), "r"(r2), "r"(r3) : "memory");
}
__device__ __forceinline__ void mma_16816(float& d0, float& d1, float& d2, float& d3,
                                          uint32_t a0, uint32_t a1, uint32_t a2, uint32_t a3, uint32_t b0, uint32_t b1) {
  asm volatile("mma.sync.aligned.m16n8k16.row.col.f32.bf16.bf16.f32 {%0,%1,%2,%3}, {%4,%5,%6,%7}, {%8,%9}, {%0,%1,%2,%3};"
    : "+f"(d0), "+f"(d1), "+f"(d2), "+f"(d3) : "r"(a0), "r"(a1), "r"(a2), "r"(a3), "r"(b0), "r"(b1));
}
__device__ __forceinline__ uint4 lds128(uint32_t addr) {
  uint4 v; asm volatile("ld.shared.v4.u32 {%0,%1,%2,%3}, [%4];" : "=r"(v.x), "=r"(v.y), "=r"(v.z), "=r"(v.w) : "r"(addr) : "memory");
  return v;
}

__device__ __forceinline__ void wgmma_n192_ss(float (&d)[96], uint64_t da, uint64_t db, int scale_d) {
  asm volatile("{\n.reg .pred p;\nsetp.ne.b32 p, %98, 0;\n"
    "wgmma.mma_async.sync.aligned.m64n192k16.f32.bf16.bf16 {%0, %1, %2, %3, %4, %5, %6, %7, %8, %9, %10, %11, %12, %13, %14, %15, %16, %17, %18, %19, %20, %21, %22, %23, %24, %25, %26, %27, %28, %29, %30, %31, %32, %33, %34, %35, %36, %37, %38, %39, %40, %41, %42, %43, %44, %45, %46, %47, %48, %49, %50, %51, %52, %53, %54, %55, %56, %57, %58, %59, %60, %61, %62, %63, %64, %65, %66, %67, %68, %69, %70, %71, %72, %73, %74, %75, %76, %77, %78, %79, %80, %81, %82, %83, %84, %85, %86, %87, %88, %89, %90, %91, %92, %93, %94, %95}, %96, %97, p, 1, 1, 0, 0;\n}\n"
    : "+f"(d[0]), "+f"(d[1]), "+f"(d[2]), "+f"(d[3]), "+f"(d[4]), "+f"(d[5]), "+f"(d[6]), "+f"(d[7]), "+f"(d[8]), "+f"(d[9]), "+f"(d[10]), "+f"(d[11]), "+f"(d[12]), "+f"(d[13]), "+f"(d[14]), "+f"(d[15]), "+f"(d[16]), "+f"(d[17]), "+f"(d[18]), "+f"(d[19]), "+f"(d[20]), "+f"(d[21]), "+f"(d[22]), "+f"(d[23]), "+f"(d[24]), "+f"(d[25]), "+f"(d[26]), "+f"(d[27]), "+f"(d[28]), "+f"(d[29]), "+f"(d[30]), "+f"(d[31]), "+f"(d[32]), "+f"(d[33]), "+f"(d[34]), "+f"(d[35]), "+f"(d[36]), "+f"(d[37]), "+f"(d[38]), "+f"(d[39]), "+f"(d[40]), "+f"(d[41]), "+f"(d[42]), "+f"(d[43]), "+f"(d[44]), "+f"(d[45]), "+f"(d[46]), "+f"(d[47]), "+f"(d[48]), "+f"(d[49]), "+f"(d[50]), "+f"(d[51]), "+f"(d[52]), "+f"(d[53]), "+f"(d[54]), "+f"(d[55]), "+f"(d[56]), "+f"(d[57]), "+f"(d[58]), "+f"(d[59]), "+f"(d[60]), "+f"(d[61]), "+f"(d[62]), "+f"(d[63]), "+f"(d[64]), "+f"(d[65]), "+f"(d[66]), "+f"(d[67]), "+f"(d[68]), "+f"(d[69]), "+f"(d[70]), "+f"(d[71]), "+f"(d[72]), "+f"(d[73]), "+f"(d[74]), "+f"(d[75]), "+f"(d[76]), "+f"(d[77]), "+f"(d[78]), "+f"(d[79]), "+f"(d[80]), "+f"(d[81]), "+f"(d[82]), "+f"(d[83]), "+f"(d[84]), "+f"(d[85]), "+f"(d[86]), "+f"(d[87]), "+f"(d[88]), "+f"(d[89]), "+f"(d[90]), "+f"(d[91]), "+f"(d[92]), "+f"(d[93]), "+f"(d[94]), "+f"(d[95])
    : "l"(da), "l"(db), "r"(scale_d));
}

__device__ __forceinline__ void wgmma_n192_rs(float (&d)[96], uint32_t a0, uint32_t a1, uint32_t a2, uint32_t a3, uint64_t db, int scale_d) {
  asm volatile("{\n.reg .pred p;\nsetp.ne.b32 p, %101, 0;\n"
    "wgmma.mma_async.sync.aligned.m64n192k16.f32.bf16.bf16 {%0, %1, %2, %3, %4, %5, %6, %7, %8, %9, %10, %11, %12, %13, %14, %15, %16, %17, %18, %19, %20, %21, %22, %23, %24, %25, %26, %27, %28, %29, %30, %31, %32, %33, %34, %35, %36, %37, %38, %39, %40, %41, %42, %43, %44, %45, %46, %47, %48, %49, %50, %51, %52, %53, %54, %55, %56, %57, %58, %59, %60, %61, %62, %63, %64, %65, %66, %67, %68, %69, %70, %71, %72, %73, %74, %75, %76, %77, %78, %79, %80, %81, %82, %83, %84, %85, %86, %87, %88, %89, %90, %91, %92, %93, %94, %95}, {%96, %97, %98, %99}, %100, p, 1, 1, 0;\n}\n"
    : "+f"(d[0]), "+f"(d[1]), "+f"(d[2]), "+f"(d[3]), "+f"(d[4]), "+f"(d[5]), "+f"(d[6]), "+f"(d[7]), "+f"(d[8]), "+f"(d[9]), "+f"(d[10]), "+f"(d[11]), "+f"(d[12]), "+f"(d[13]), "+f"(d[14]), "+f"(d[15]), "+f"(d[16]), "+f"(d[17]), "+f"(d[18]), "+f"(d[19]), "+f"(d[20]), "+f"(d[21]), "+f"(d[22]), "+f"(d[23]), "+f"(d[24]), "+f"(d[25]), "+f"(d[26]), "+f"(d[27]), "+f"(d[28]), "+f"(d[29]), "+f"(d[30]), "+f"(d[31]), "+f"(d[32]), "+f"(d[33]), "+f"(d[34]), "+f"(d[35]), "+f"(d[36]), "+f"(d[37]), "+f"(d[38]), "+f"(d[39]), "+f"(d[40]), "+f"(d[41]), "+f"(d[42]), "+f"(d[43]), "+f"(d[44]), "+f"(d[45]), "+f"(d[46]), "+f"(d[47]), "+f"(d[48]), "+f"(d[49]), "+f"(d[50]), "+f"(d[51]), "+f"(d[52]), "+f"(d[53]), "+f"(d[54]), "+f"(d[55]), "+f"(d[56]), "+f"(d[57]), "+f"(d[58]), "+f"(d[59]), "+f"(d[60]), "+f"(d[61]), "+f"(d[62]), "+f"(d[63]), "+f"(d[64]), "+f"(d[65]), "+f"(d[66]), "+f"(d[67]), "+f"(d[68]), "+f"(d[69]), "+f"(d[70]), "+f"(d[71]), "+f"(d[72]), "+f"(d[73]), "+f"(d[74]), "+f"(d[75]), "+f"(d[76]), "+f"(d[77]), "+f"(d[78]), "+f"(d[79]), "+f"(d[80]), "+f"(d[81]), "+f"(d[82]), "+f"(d[83]), "+f"(d[84]), "+f"(d[85]), "+f"(d[86]), "+f"(d[87]), "+f"(d[88]), "+f"(d[89]), "+f"(d[90]), "+f"(d[91]), "+f"(d[92]), "+f"(d[93]), "+f"(d[94]), "+f"(d[95])
    : "r"(a0), "r"(a1), "r"(a2), "r"(a3), "l"(db), "r"(scale_d));
}

__device__ __forceinline__ void wgmma_n192_rs_tb(float (&d)[96], uint32_t a0, uint32_t a1, uint32_t a2, uint32_t a3, uint64_t db, int scale_d) {
  asm volatile("{\n.reg .pred p;\nsetp.ne.b32 p, %101, 0;\n"
    "wgmma.mma_async.sync.aligned.m64n192k16.f32.bf16.bf16 {%0, %1, %2, %3, %4, %5, %6, %7, %8, %9, %10, %11, %12, %13, %14, %15, %16, %17, %18, %19, %20, %21, %22, %23, %24, %25, %26, %27, %28, %29, %30, %31, %32, %33, %34, %35, %36, %37, %38, %39, %40, %41, %42, %43, %44, %45, %46, %47, %48, %49, %50, %51, %52, %53, %54, %55, %56, %57, %58, %59, %60, %61, %62, %63, %64, %65, %66, %67, %68, %69, %70, %71, %72, %73, %74, %75, %76, %77, %78, %79, %80, %81, %82, %83, %84, %85, %86, %87, %88, %89, %90, %91, %92, %93, %94, %95}, {%96, %97, %98, %99}, %100, p, 1, 1, 1;\n}\n"
    : "+f"(d[0]), "+f"(d[1]), "+f"(d[2]), "+f"(d[3]), "+f"(d[4]), "+f"(d[5]), "+f"(d[6]), "+f"(d[7]), "+f"(d[8]), "+f"(d[9]), "+f"(d[10]), "+f"(d[11]), "+f"(d[12]), "+f"(d[13]), "+f"(d[14]), "+f"(d[15]), "+f"(d[16]), "+f"(d[17]), "+f"(d[18]), "+f"(d[19]), "+f"(d[20]), "+f"(d[21]), "+f"(d[22]), "+f"(d[23]), "+f"(d[24]), "+f"(d[25]), "+f"(d[26]), "+f"(d[27]), "+f"(d[28]), "+f"(d[29]), "+f"(d[30]), "+f"(d[31]), "+f"(d[32]), "+f"(d[33]), "+f"(d[34]), "+f"(d[35]), "+f"(d[36]), "+f"(d[37]), "+f"(d[38]), "+f"(d[39]), "+f"(d[40]), "+f"(d[41]), "+f"(d[42]), "+f"(d[43]), "+f"(d[44]), "+f"(d[45]), "+f"(d[46]), "+f"(d[47]), "+f"(d[48]), "+f"(d[49]), "+f"(d[50]), "+f"(d[51]), "+f"(d[52]), "+f"(d[53]), "+f"(d[54]), "+f"(d[55]), "+f"(d[56]), "+f"(d[57]), "+f"(d[58]), "+f"(d[59]), "+f"(d[60]), "+f"(d[61]), "+f"(d[62]), "+f"(d[63]), "+f"(d[64]), "+f"(d[65]), "+f"(d[66]), "+f"(d[67]), "+f"(d[68]), "+f"(d[69]), "+f"(d[70]), "+f"(d[71]), "+f"(d[72]), "+f"(d[73]), "+f"(d[74]), "+f"(d[75]), "+f"(d[76]), "+f"(d[77]), "+f"(d[78]), "+f"(d[79]), "+f"(d[80]), "+f"(d[81]), "+f"(d[82]), "+f"(d[83]), "+f"(d[84]), "+f"(d[85]), "+f"(d[86]), "+f"(d[87]), "+f"(d[88]), "+f"(d[89]), "+f"(d[90]), "+f"(d[91]), "+f"(d[92]), "+f"(d[93]), "+f"(d[94]), "+f"(d[95])
    : "r"(a0), "r"(a1), "r"(a2), "r"(a3), "l"(db), "r"(scale_d));
}

__device__ __forceinline__ void wgmma_n56_rs(float (&d)[28], uint32_t a0, uint32_t a1, uint32_t a2, uint32_t a3, uint64_t db, int scale_d) {
  asm volatile("{\n.reg .pred p;\nsetp.ne.b32 p, %33, 0;\n"
    "wgmma.mma_async.sync.aligned.m64n56k16.f32.bf16.bf16 {%0, %1, %2, %3, %4, %5, %6, %7, %8, %9, %10, %11, %12, %13, %14, %15, %16, %17, %18, %19, %20, %21, %22, %23, %24, %25, %26, %27}, {%28, %29, %30, %31}, %32, p, 1, 1, 0;\n}\n"
    : "+f"(d[0]), "+f"(d[1]), "+f"(d[2]), "+f"(d[3]), "+f"(d[4]), "+f"(d[5]), "+f"(d[6]), "+f"(d[7]), "+f"(d[8]), "+f"(d[9]), "+f"(d[10]), "+f"(d[11]), "+f"(d[12]), "+f"(d[13]), "+f"(d[14]), "+f"(d[15]), "+f"(d[16]), "+f"(d[17]), "+f"(d[18]), "+f"(d[19]), "+f"(d[20]), "+f"(d[21]), "+f"(d[22]), "+f"(d[23]), "+f"(d[24]), "+f"(d[25]), "+f"(d[26]), "+f"(d[27])
    : "r"(a0), "r"(a1), "r"(a2), "r"(a3), "l"(db), "r"(scale_d));
}

__device__ __forceinline__ void acc_fence(float (&d)[96]) {
  asm volatile("" : "+f"(d[0]), "+f"(d[1]), "+f"(d[2]), "+f"(d[3]), "+f"(d[4]), "+f"(d[5]), "+f"(d[6]), "+f"(d[7]), "+f"(d[8]), "+f"(d[9]), "+f"(d[10]), "+f"(d[11]), "+f"(d[12]), "+f"(d[13]), "+f"(d[14]), "+f"(d[15]), "+f"(d[16]), "+f"(d[17]), "+f"(d[18]), "+f"(d[19]), "+f"(d[20]), "+f"(d[21]), "+f"(d[22]), "+f"(d[23]), "+f"(d[24]), "+f"(d[25]), "+f"(d[26]), "+f"(d[27]), "+f"(d[28]), "+f"(d[29]), "+f"(d[30]), "+f"(d[31]), "+f"(d[32]), "+f"(d[33]), "+f"(d[34]), "+f"(d[35]), "+f"(d[36]), "+f"(d[37]), "+f"(d[38]), "+f"(d[39]), "+f"(d[40]), "+f"(d[41]), "+f"(d[42]), "+f"(d[43]), "+f"(d[44]), "+f"(d[45]), "+f"(d[46]), "+f"(d[47]), "+f"(d[48]), "+f"(d[49]), "+f"(d[50]), "+f"(d[51]), "+f"(d[52]), "+f"(d[53]), "+f"(d[54]), "+f"(d[55]), "+f"(d[56]), "+f"(d[57]), "+f"(d[58]), "+f"(d[59]), "+f"(d[60]), "+f"(d[61]), "+f"(d[62]), "+f"(d[63]), "+f"(d[64]), "+f"(d[65]), "+f"(d[66]), "+f"(d[67]), "+f"(d[68]), "+f"(d[69]), "+f"(d[70]), "+f"(d[71]), "+f"(d[72]), "+f"(d[73]), "+f"(d[74]), "+f"(d[75]), "+f"(d[76]), "+f"(d[77]), "+f"(d[78]), "+f"(d[79]), "+f"(d[80]), "+f"(d[81]), "+f"(d[82]), "+f"(d[83]), "+f"(d[84]), "+f"(d[85]), "+f"(d[86]), "+f"(d[87]), "+f"(d[88]), "+f"(d[89]), "+f"(d[90]), "+f"(d[91]), "+f"(d[92]), "+f"(d[93]), "+f"(d[94]), "+f"(d[95]) :: "memory");
}

__device__ __forceinline__ void acc_fence(float (&d)[28]) {
  asm volatile("" : "+f"(d[0]), "+f"(d[1]), "+f"(d[2]), "+f"(d[3]), "+f"(d[4]), "+f"(d[5]), "+f"(d[6]), "+f"(d[7]), "+f"(d[8]), "+f"(d[9]), "+f"(d[10]), "+f"(d[11]), "+f"(d[12]), "+f"(d[13]), "+f"(d[14]), "+f"(d[15]), "+f"(d[16]), "+f"(d[17]), "+f"(d[18]), "+f"(d[19]), "+f"(d[20]), "+f"(d[21]), "+f"(d[22]), "+f"(d[23]), "+f"(d[24]), "+f"(d[25]), "+f"(d[26]), "+f"(d[27]) :: "memory");
}


__global__ void __launch_bounds__(192) fold_weights_kernel(const __nv_bfloat16* __restrict__ wqkv_t, const __nv_bfloat16* __restrict__ wo_t,
                                    const __nv_bfloat16* __restrict__ wqkv_s, const __nv_bfloat16* __restrict__ wo_s) {
  __shared__ float cmA[CH];
  __shared__ float Bs[16][CH + 4];
  const int mat = blockIdx.y, n0 = blockIdx.x * 16, tid = threadIdx.x;
  const __nv_bfloat16* wqkv = (mat < 2) ? wqkv_t : wqkv_s;
  const __nv_bfloat16* wo = (mat < 2) ? wo_t : wo_s;
  const bool isM = (mat & 1) == 0;
  const int offA = isM ? 0 : 2 * CH;
  {
    float s = 0.f, s2 = 0.f;
    for (int a = 0; a < CH; a++) {
      s += __bfloat162float(wqkv[a * 3 * CH + offA + tid]);
      if (isM) s2 += __bfloat162float(wqkv[a * 3 * CH + CH + tid]);
    }
    cmA[tid] = s * (1.0f / CH);
    const float cmB = s2 * (1.0f / CH);
    for (int n = 0; n < 16; n++) {
      Bs[n][tid] = isM ? (__bfloat162float(wqkv[(n0 + n) * 3 * CH + CH + tid]) - cmB)
                       : __bfloat162float(wo[tid * CH + n0 + n]);
    }
  }
  __syncthreads();
  float acc[16];
#pragma unroll
  for (int n = 0; n < 16; n++) acc[n] = 0.f;
  const __nv_bfloat16* arow = wqkv + tid * 3 * CH + offA;
  for (int c = 0; c < CH; c += 4) {
    float a[4];
#pragma unroll
    for (int i = 0; i < 4; i++) a[i] = __bfloat162float(arow[c + i]) - cmA[c + i];
#pragma unroll
    for (int n = 0; n < 16; n++) {
      const float4 b = *reinterpret_cast<const float4*>(&Bs[n][c]);
      acc[n] = fmaf(a[0], b.x, acc[n]); acc[n] = fmaf(a[1], b.y, acc[n]);
      acc[n] = fmaf(a[2], b.z, acc[n]); acc[n] = fmaf(a[3], b.w, acc[n]);
    }
  }
  const int k = tid, p = k >> 6, kc = k & 63;
#pragma unroll
  for (int n = 0; n < 16; n++) {
    const int nn = n0 + n;
    g_w[mat][p * (CH * 64) + nn * 64 + (((kc >> 3) ^ (nn & 7)) << 3) + (kc & 7)] = __float2bfloat16(acc[n]);
  }
}

struct Params {
  int role;
};

__device__ __forceinline__ uint32_t frag_addr(uint32_t slot_rowoff, uint32_t sw, int hiblk, int kk) {
  const int ci = 2 * kk + hiblk;
  return slot_rowoff + (ci >> 3) * PANEL_X + ((((uint32_t)ci & 7u) ^ sw) << 4);
}

__device__ __forceinline__ float row_rstd(uint32_t slot, int w, int lane) {
  const int row = 16 * w + (lane >> 1), half = lane & 1;
  const uint32_t rbase = slot + row * 128, sw = row & 7;
  float s = 0.f, ss = 0.f;
#pragma unroll
  for (int i = 0; i < 12; i++) {
    const int c = half * 12 + i;
    const uint4 v = lds128(rbase + (c >> 3) * PANEL_X + ((((uint32_t)c & 7u) ^ sw) << 4));
    const uint32_t u[4] = {v.x, v.y, v.z, v.w};
#pragma unroll
    for (int e = 0; e < 4; e++) {
      const float lo = bf_lo(u[e]), hi = bf_hi(u[e]);
      s += lo; s += hi;
      ss = fmaf(lo, lo, ss); ss = fmaf(hi, hi, ss);
    }
  }
  s += __shfl_xor_sync(0xffffffffu, s, 1);
  ss += __shfl_xor_sync(0xffffffffu, ss, 1);
  const float mean = s * (1.0f / CH);
  const float var = fmaxf(ss * (1.0f / CH) - mean * mean, 0.f);
  return rsqrtf(var + 1e-5f);
}

__global__ void __launch_bounds__(NWG * 128, 1)
swin_main_kernel(const __grid_constant__ CUtensorMap map_in, const __grid_constant__ CUtensorMap map_out, const int role) {
  extern __shared__ __align__(1024) uint8_t smem_raw[];
  const uint32_t sbase = smem_u32(smem_raw);
  const int tid = threadIdx.x, wg = tid >> 7, t128 = tid & 127, w = t128 >> 5, lane = tid & 31;
  const int g = lane >> 2, q = lane & 3;

  const uint32_t bar_w = sbase + SMEM_MISC;
  const uint32_t bar_full = sbase + SMEM_MISC + 8 + 8 * wg;
  const uint32_t slot = sbase + SMEM_SLOT + wg * SLOT_BYTES;
  float* rbuf = reinterpret_cast<float*>(smem_raw + SMEM_RBUF) + wg * 64;

  if (tid == 0) {
    mbar_init(bar_w, 1);
    for (int i = 0; i < NWG; i++) mbar_init(sbase + SMEM_MISC + 8 + 8 * i, 1);
    asm volatile("fence.mbarrier_init.release.cluster;" ::: "memory");
  }
  for (int i = tid; i < NWG * SLOT_BYTES / 16; i += NWG * 128)
    *reinterpret_cast<uint4*>(smem_raw + SMEM_SLOT + i * 16) = make_uint4(0, 0, 0, 0);
  fence_proxy_async();
  __syncthreads();

  if (tid == 0) {
    mbar_expect_tx(bar_w, 2 * WMAT_BYTES);
    bulk_load(sbase + SMEM_W0, &g_w[role * 2][0], WMAT_BYTES, bar_w);
    bulk_load(sbase + SMEM_W1, &g_w[role * 2 + 1][0], WMAT_BYTES, bar_w);
  }

  const int nunits = role == 0 ? NTILE_A : NUNIT_B;
  const int nworkers = gridDim.x * NWG;
  const int worker = blockIdx.x * NWG + wg;
  const uint32_t tx_bytes = role == 0 ? SLOT_BYTES : 3 * 49 * 128;

  auto issue_load = [&](int u) {
    int c1, c2, c3;
    if (role == 0) { c1 = 0; c2 = (u % 14) * 16; c3 = u / 14; }
    else { const int t = u & 3, wx = (u >> 2) & 31, wy = u >> 7; c1 = wx * 7; c2 = wy * 7; c3 = t; }
    mbar_expect_tx(bar_full, tx_bytes);
#pragma unroll
    for (int p = 0; p < 3; p++) tma_load_4d(slot + p * PANEL_X, &map_in, p * 64, c1, c2, c3, bar_full);
  };

  if (t128 == 0 && worker < nunits) issue_load(worker);
  __syncwarp();
  mbar_wait(bar_w, 0);

  const int blk = lane >> 3;
  const int frow = 16 * w + (lane & 7) + ((blk & 1) << 3);
  const uint32_t frowoff = slot + frow * 128, fsw = frow & 7;
  const int fhi = blk >> 1;

  const uint64_t dX = make_desc(slot, 16, 1024);
  const uint64_t dW0 = make_desc(sbase + SMEM_W0, 16, 1024);
  const uint64_t dW1 = make_desc(sbase + SMEM_W1, 16, 1024);
  const uint64_t dXmn = make_desc(slot, PANEL_X, 1024);

  const float scale_l2e = 0.07216878364870322f * 1.4426950408889634f;

  uint32_t phase = 0;
  for (int u = worker; u < nunits; u += nworkers) {
    mbar_wait(bar_full, phase); phase ^= 1;

    float acc[96];
    wgmma_fence();
#pragma unroll
    for (int kk = 0; kk < 12; kk++) {
      const uint32_t off = (kk >> 2) * PANEL_X + (kk & 3) * 32;
      const uint32_t offw = (kk >> 2) * PANEL_W + (kk & 3) * 32;
      wgmma_n192_ss(acc, dX + (off >> 4), dW0 + (offw >> 4), kk);
    }
    wgmma_commit();
    const float rmine = row_rstd(slot, w, lane);
    uint32_t fr[48];

    if (role == 0) {
      wgmma_wait0(); acc_fence(acc);
#pragma unroll
      for (int i = 0; i < 48; i++) fr[i] = pack_bf16(acc[2 * i], acc[2 * i + 1]);
      float d0[4] = {0.f, 0.f, 0.f, 0.f}, d1[4] = {0.f, 0.f, 0.f, 0.f};
#pragma unroll
      for (int kk = 0; kk < 12; kk++) {
        uint32_t b0, b1, b2, b3;
        ldsm_x4(frag_addr(frowoff, fsw, fhi, kk), b0, b1, b2, b3);
        mma_16816(d0[0], d0[1], d0[2], d0[3], fr[4 * kk], fr[4 * kk + 1], fr[4 * kk + 2], fr[4 * kk + 3], b0, b2);
        mma_16816(d1[0], d1[1], d1[2], d1[3], fr[4 * kk], fr[4 * kk + 1], fr[4 * kk + 2], fr[4 * kk + 3], b1, b3);
      }
      const float rA = __shfl_sync(0xffffffffu, rmine, 2 * g);
      const float rB = __shfl_sync(0xffffffffu, rmine, 2 * g + 16);
      const float k0 = __shfl_sync(0xffffffffu, rmine, 4 * q);
      const float k1 = __shfl_sync(0xffffffffu, rmine, 4 * q + 2);
      const float k2 = __shfl_sync(0xffffffffu, rmine, 4 * q + 16);
      const float k3 = __shfl_sync(0xffffffffu, rmine, 4 * q + 18);
      const bool valid = (g >> 2) == (q >> 1);
      float sa0 = d0[0] * k0 * (rA * scale_l2e), sa1 = d0[1] * k1 * (rA * scale_l2e);
      float sb0 = d1[2] * k2 * (rB * scale_l2e), sb1 = d1[3] * k3 * (rB * scale_l2e);
      float ma = fmaxf(sa0, sa1), mb = fmaxf(sb0, sb1);
      ma = fmaxf(ma, __shfl_xor_sync(0xffffffffu, ma, 1));
      mb = fmaxf(mb, __shfl_xor_sync(0xffffffffu, mb, 1));
      const float ea0 = exp2f(sa0 - ma), ea1 = exp2f(sa1 - ma);
      const float eb0 = exp2f(sb0 - mb), eb1 = exp2f(sb1 - mb);
      float suma = ea0 + ea1, sumb = eb0 + eb1;
      suma += __shfl_xor_sync(0xffffffffu, suma, 1);
      sumb += __shfl_xor_sync(0xffffffffu, sumb, 1);
      const float ia = __fdividef(1.f, suma), ib = __fdividef(1.f, sumb);
      const uint32_t pa0 = valid ? pack_bf16(ea0 * ia * k0, ea1 * ia * k1) : 0u;
      const uint32_t pa3 = valid ? pack_bf16(eb0 * ib * k2, eb1 * ib * k3) : 0u;
#pragma unroll
      for (int jj = 0; jj < 12; jj++) {
        uint32_t b0, b1, b2, b3;
        ldsm_x4_t(frag_addr(frowoff, fsw, fhi, jj), b0, b1, b2, b3);
        acc[8 * jj + 0] = 0.f; acc[8 * jj + 1] = 0.f; acc[8 * jj + 2] = 0.f; acc[8 * jj + 3] = 0.f;
        acc[8 * jj + 4] = 0.f; acc[8 * jj + 5] = 0.f; acc[8 * jj + 6] = 0.f; acc[8 * jj + 7] = 0.f;
        mma_16816(acc[8 * jj + 0], acc[8 * jj + 1], acc[8 * jj + 2], acc[8 * jj + 3], pa0, 0u, 0u, pa3, b0, b1);
        mma_16816(acc[8 * jj + 4], acc[8 * jj + 5], acc[8 * jj + 6], acc[8 * jj + 7], pa0, 0u, 0u, pa3, b2, b3);
      }
    } else {
      if ((lane & 1) == 0) rbuf[16 * w + (lane >> 1)] = rmine;
      wg_bar(1 + wg);
      wgmma_wait0(); acc_fence(acc);
#pragma unroll
      for (int i = 0; i < 48; i++) fr[i] = pack_bf16(acc[2 * i], acc[2 * i + 1]);
      float s[28];
      wgmma_fence();
#pragma unroll
      for (int kk = 0; kk < 12; kk++) {
        const uint32_t off = (kk >> 2) * PANEL_X + (kk & 3) * 32;
        wgmma_n56_rs(s, fr[4 * kk], fr[4 * kk + 1], fr[4 * kk + 2], fr[4 * kk + 3], dX + (off >> 4), kk);
      }
      wgmma_commit();
      float rj[14];
#pragma unroll
      for (int j = 0; j < 7; j++) {
        const float2 v = *reinterpret_cast<const float2*>(&rbuf[8 * j + 2 * q]);
        rj[2 * j] = v.x; rj[2 * j + 1] = v.y;
      }
      const float ri0 = rbuf[16 * w + g] * scale_l2e, ri1 = rbuf[16 * w + g + 8] * scale_l2e;
      wgmma_wait0(); acc_fence(s);
      float m0 = -INFINITY, m1 = -INFINITY;
#pragma unroll
      for (int j = 0; j < 7; j++) {
#pragma unroll
        for (int e = 0; e < 2; e++) {
          const bool ok = (j < 6) || (2 * q + e == 0);
          float v0 = s[4 * j + e] * rj[2 * j + e] * ri0;
          float v1 = s[4 * j + 2 + e] * rj[2 * j + e] * ri1;
          v0 = ok ? v0 : -INFINITY; v1 = ok ? v1 : -INFINITY;
          s[4 * j + e] = v0; s[4 * j + 2 + e] = v1;
          m0 = fmaxf(m0, v0); m1 = fmaxf(m1, v1);
        }
      }
      m0 = fmaxf(m0, __shfl_xor_sync(0xffffffffu, m0, 1)); m0 = fmaxf(m0, __shfl_xor_sync(0xffffffffu, m0, 2));
      m1 = fmaxf(m1, __shfl_xor_sync(0xffffffffu, m1, 1)); m1 = fmaxf(m1, __shfl_xor_sync(0xffffffffu, m1, 2));
      float sum0 = 0.f, sum1 = 0.f;
#pragma unroll
      for (int j = 0; j < 7; j++) {
#pragma unroll
        for (int e = 0; e < 2; e++) {
          const float e0 = exp2f(s[4 * j + e] - m0), e1 = exp2f(s[4 * j + 2 + e] - m1);
          s[4 * j + e] = e0; s[4 * j + 2 + e] = e1;
          sum0 += e0; sum1 += e1;
        }
      }
      sum0 += __shfl_xor_sync(0xffffffffu, sum0, 1); sum0 += __shfl_xor_sync(0xffffffffu, sum0, 2);
      sum1 += __shfl_xor_sync(0xffffffffu, sum1, 1); sum1 += __shfl_xor_sync(0xffffffffu, sum1, 2);
      const float i0 = __fdividef(1.f, sum0), i1 = __fdividef(1.f, sum1);
      uint32_t pa[16];
#pragma unroll
      for (int j = 0; j < 7; j++) {
        pa[(j >> 1) * 4 + (j & 1) * 2 + 0] = pack_bf16(s[4 * j] * i0 * rj[2 * j], s[4 * j + 1] * i0 * rj[2 * j + 1]);
        pa[(j >> 1) * 4 + (j & 1) * 2 + 1] = pack_bf16(s[4 * j + 2] * i1 * rj[2 * j], s[4 * j + 3] * i1 * rj[2 * j + 1]);
      }
      pa[14] = 0u; pa[15] = 0u;
      wgmma_fence();
#pragma unroll
      for (int kk = 0; kk < 4; kk++)
        wgmma_n192_rs_tb(acc, pa[4 * kk], pa[4 * kk + 1], pa[4 * kk + 2], pa[4 * kk + 3], dXmn + ((kk * 2048) >> 4), kk);
      wgmma_commit();
      wgmma_wait0(); acc_fence(acc);
    }

#pragma unroll
    for (int i = 0; i < 48; i++) fr[i] = pack_bf16(acc[2 * i], acc[2 * i + 1]);
    wgmma_fence();
#pragma unroll
    for (int kk = 0; kk < 12; kk++) {
      const uint32_t offw = (kk >> 2) * PANEL_W + (kk & 3) * 32;
      wgmma_n192_rs(acc, fr[4 * kk], fr[4 * kk + 1], fr[4 * kk + 2], fr[4 * kk + 3], dW1 + (offw >> 4), kk);
    }
    wgmma_commit();
    wgmma_wait0(); acc_fence(acc);
    wg_bar(1 + wg);
#pragma unroll
    for (int kk = 0; kk < 12; kk++) {
      const uint32_t a = frag_addr(frowoff, fsw, fhi, kk);
      uint32_t x0, x1, x2, x3;
      ldsm_x4(a, x0, x1, x2, x3);
      const uint32_t o0 = pack_bf16(acc[8 * kk + 0] + bf_lo(x0), acc[8 * kk + 1] + bf_hi(x0));
      const uint32_t o1 = pack_bf16(acc[8 * kk + 2] + bf_lo(x1), acc[8 * kk + 3] + bf_hi(x1));
      const uint32_t o2 = pack_bf16(acc[8 * kk + 4] + bf_lo(x2), acc[8 * kk + 5] + bf_hi(x2));
      const uint32_t o3 = pack_bf16(acc[8 * kk + 6] + bf_lo(x3), acc[8 * kk + 7] + bf_hi(x3));
      stsm_x4(a, o0, o1, o2, o3);
    }
    fence_proxy_async();
    wg_bar(1 + wg);
    if (t128 == 0) {
      int c1, c2, c3;
      if (role == 0) { c1 = 0; c2 = (u % 14) * 16; c3 = u / 14; }
      else { const int t = u & 3, wx = (u >> 2) & 31, wy = u >> 7; c1 = wx * 7; c2 = wy * 7; c3 = t; }
#pragma unroll
      for (int p = 0; p < 3; p++) tma_store_4d(&map_out, slot + p * PANEL_X, p * 64, c1, c2, c3);
      bulk_commit();
      bulk_wait_read0();
      if (u + nworkers < nunits) issue_load(u + nworkers);
    }
    __syncwarp();
  }
  if (t128 == 0) bulk_wait0();
}

typedef CUresult (*EncodeTiledFn)(CUtensorMap*, CUtensorMapDataType, cuuint32_t, void*, const cuuint64_t*, const cuuint64_t*,
                                  const cuuint32_t*, const cuuint32_t*, CUtensorMapInterleave, CUtensorMapSwizzle,
                                  CUtensorMapL2promotion, CUtensorMapFloatOOBfill);

bool make_map(EncodeTiledFn fn, CUtensorMap* m, void* base, bool pixel_major) {
  cuuint64_t dims[4]; cuuint64_t strides[3]; cuuint32_t box[4]; cuuint32_t es[4] = {1, 1, 1, 1};
  const cuuint64_t sC = (cuuint64_t)CH * 2, sW = sC * WW, sT = sW * HH;
  if (pixel_major) {
    dims[0] = CH; dims[1] = TT; dims[2] = WW; dims[3] = HH;
    strides[0] = sT; strides[1] = sC; strides[2] = sW;
    box[0] = 64; box[1] = 4; box[2] = 16; box[3] = 1;
  } else {
    dims[0] = CH; dims[1] = WW; dims[2] = HH; dims[3] = TT;
    strides[0] = sC; strides[1] = sW; strides[2] = sT;
    box[0] = 64; box[1] = 7; box[2] = 7; box[3] = 1;
  }
  return fn(m, CU_TENSOR_MAP_DATA_TYPE_BFLOAT16, 4, base, dims, strides, box, es, CU_TENSOR_MAP_INTERLEAVE_NONE,
            CU_TENSOR_MAP_SWIZZLE_128B, CU_TENSOR_MAP_L2_PROMOTION_L2_256B, CU_TENSOR_MAP_FLOAT_OOB_FILL_NONE) == CUDA_SUCCESS;
}

}

extern "C" void kernel_launch(void* const* d_in, const int* in_sizes, int n_in, void* d_out, int out_size) {
  const __nv_bfloat16* x = (const __nv_bfloat16*)d_in[0];
  const __nv_bfloat16* wqkv_t = (const __nv_bfloat16*)d_in[1];
  const __nv_bfloat16* wo_t = (const __nv_bfloat16*)d_in[2];
  const __nv_bfloat16* wqkv_s = (const __nv_bfloat16*)d_in[3];
  const __nv_bfloat16* wo_s = (const __nv_bfloat16*)d_in[4];

  static bool init = false;
  static CUtensorMap mA_in, mA_out, mB_in, mB_out;
  static void* last_x = nullptr; static void* last_out = nullptr;
  static int nsm = 132;
  if (!init || last_x != d_in[0] || last_out != d_out) {
    void* fnp = nullptr; cudaDriverEntryPointQueryResult qr;
    cudaGetDriverEntryPoint("cuTensorMapEncodeTiled", &fnp, cudaEnableDefault, &qr);
    EncodeTiledFn fn = (EncodeTiledFn)fnp;
    void* x1p = nullptr; cudaGetSymbolAddress(&x1p, g_x1);
    make_map(fn, &mA_in, (void*)x, true);
    make_map(fn, &mA_out, x1p, true);
    make_map(fn, &mB_in, x1p, false);
    make_map(fn, &mB_out, d_out, false);
    cudaFuncSetAttribute(swin_main_kernel, cudaFuncAttributeMaxDynamicSharedMemorySize, SMEM_TOTAL);
    cudaDeviceGetAttribute(&nsm, cudaDevAttrMultiProcessorCount, 0);
    init = true; last_x = d_in[0]; last_out = d_out;
  }
  fold_weights_kernel<<<dim3(12, 4), 192>>>(wqkv_t, wo_t, wqkv_s, wo_s);
  swin_main_kernel<<<nsm, NWG * 128, SMEM_TOTAL>>>(mA_in, mA_out, 0);
  swin_main_kernel<<<nsm, NWG * 128, SMEM_TOTAL>>>(mB_in, mB_out, 1);
}
```

```cpp
#include <cuda_runtime.h>
#include <cuda_bf16.h>
#include <cuda.h>
#include <stdint.h>

namespace {

constexpr int CH = 192;
constexpr int TT = 4, HH = 224, WW = 224;
constexpr int NTOK = TT * HH * WW;
constexpr int PANEL_X = 64 * 128;
constexpr int SLOT_BYTES = 3 * PANEL_X;
constexpr int PANEL_W = 192 * 128;
constexpr int WMAT_BYTES = 3 * PANEL_W;
constexpr int NWG = 2;
constexpr int NSLOT = 3;
constexpr int SMEM_W0 = 0;
constexpr int SMEM_W1 = WMAT_BYTES;
constexpr int SMEM_SLOT = 2 * WMAT_BYTES;
constexpr int SMEM_MISC = SMEM_SLOT + NSLOT * SLOT_BYTES;
constexpr int SMEM_RBUF = SMEM_MISC + 64;
constexpr int SMEM_TOTAL = SMEM_RBUF + NWG * 64 * 4;

constexpr int NTILE_A = HH * (WW / 16);
constexpr int NUNIT_B = 32 * 32 * 4;

__device__ __nv_bfloat16 g_x1[(size_t)NTOK * CH];
__device__ __align__(1024) __nv_bfloat16 g_w[4][CH * CH];

__device__ __forceinline__ uint32_t smem_u32(const void* p) { return (uint32_t)__cvta_generic_to_shared(p); }

__device__ __forceinline__ void mbar_init(uint32_t bar, uint32_t count) {
  asm volatile("mbarrier.init.shared::cta.b64 [%0], %1;" :: "r"(bar), "r"(count));
}
__device__ __forceinline__ void mbar_expect_tx(uint32_t bar, uint32_t bytes) {
  asm volatile("mbarrier.arrive.expect_tx.shared::cta.b64 _, [%0], %1;" :: "r"(bar), "r"(bytes) : "memory");
}
__device__ __forceinline__ void mbar_wait(uint32_t bar, uint32_t parity) {
  asm volatile(
    "{\n.reg .pred p;\n"
    "WAIT_%=:\n"
    "mbarrier.try_wait.parity.shared::cta.b64 p, [%0], %1;\n"
    "@p bra DONE_%=;\n"
    "bra WAIT_%=;\n"
    "DONE_%=:\n}\n" :: "r"(bar), "r"(parity) : "memory");
}
__device__ __forceinline__ void tma_load_4d(uint32_t dst, const CUtensorMap* map, int c0, int c1, int c2, int c3, uint32_t bar) {
  asm volatile("cp.async.bulk.tensor.4d.shared::cluster.global.tile.mbarrier::complete_tx::bytes [%0], [%1, {%2, %3, %4, %5}], [%6];"
    :: "r"(dst), "l"(map), "r"(c0), "r"(c1), "r"(c2), "r"(c3), "r"(bar) : "memory");
}
__device__ __forceinline__ void tma_prefetch_4d(const CUtensorMap* map, int c0, int c1, int c2, int c3) {
  asm volatile("cp.async.bulk.prefetch.tensor.4d.L2.global.tile [%0, {%1, %2, %3, %4}];"
    :: "l"(map), "r"(c0), "r"(c1), "r"(c2), "r"(c3) : "memory");
}
__device__ __forceinline__ void tma_store_4d(const CUtensorMap* map, uint32_t src, int c0, int c1, int c2, int c3) {
  asm volatile("cp.async.bulk.tensor.4d.global.shared::cta.tile.bulk_group [%0, {%1, %2, %3, %4}], [%5];"
    :: "l"(map), "r"(c0), "r"(c1), "r"(c2), "r"(c3), "r"(src) : "memory");
}
__device__ __forceinline__ void bulk_load(uint32_t dst, const void* src, uint32_t bytes, uint32_t bar) {
  asm volatile("cp.async.bulk.shared::cluster.global.mbarrier::complete_tx::bytes [%0], [%1], %2, [%3];"
    :: "r"(dst), "l"(src), "r"(bytes), "r"(bar) : "memory");
}
__device__ __forceinline__ void bulk_commit() { asm volatile("cp.async.bulk.commit_group;" ::: "memory"); }
__device__ __forceinline__ void bulk_wait_read0() { asm volatile("cp.async.bulk.wait_group.read 0;" ::: "memory"); }
__device__ __forceinline__ void bulk_wait0() { asm volatile("cp.async.bulk.wait_group 0;" ::: "memory"); }
__device__ __forceinline__ void fence_proxy_async() { asm volatile("fence.proxy.async.shared::cta;" ::: "memory"); }
__device__ __forceinline__ void wg_bar(int id) { asm volatile("bar.sync %0, 128;" :: "r"(id) : "memory"); }
__device__ __forceinline__ void wgmma_fence() { asm volatile("wgmma.fence.sync.aligned;" ::: "memory"); }
__device__ __forceinline__ void wgmma_commit() { asm volatile("wgmma.commit_group.sync.aligned;" ::: "memory"); }
__device__ __forceinline__ void wgmma_wait0() { asm volatile("wgmma.wait_group.sync.aligned 0;" ::: "memory"); }

__device__ __forceinline__ uint64_t make_desc(uint32_t saddr, uint32_t lbo, uint32_t sbo) {
  return (uint64_t)((saddr & 0x3FFFF) >> 4) | ((uint64_t)((lbo & 0x3FFFF) >> 4) << 16) |
         ((uint64_t)((sbo & 0x3FFFF) >> 4) << 32) | ((uint64_t)1 << 62);
}
__device__ __forceinline__ uint32_t pack_bf16(float lo, float hi) {
  uint32_t r; asm("cvt.rn.bf16x2.f32 %0, %1, %2;" : "=r"(r) : "f"(hi), "f"(lo)); return r;
}
__device__ __forceinline__ float bf_lo(uint32_t u) { return __uint_as_float(u << 16); }
__device__ __forceinline__ float bf_hi(uint32_t u) { return __uint_as_float(u & 0xffff0000u); }
__device__ __forceinline__ void ldsm_x4(uint32_t addr, uint32_t& r0, uint32_t& r1, uint32_t& r2, uint32_t& r3) {
  asm volatile("ldmatrix.sync.aligned.m8n8.x4.shared.b16 {%0,%1,%2,%3}, [%4];"
    : "=r"(r0), "=r"(r1), "=r"(r2), "=r"(r3) : "r"(addr) : "memory");
}
__device__ __forceinline__ void ldsm_x4_t(uint32_t addr, uint32_t& r0, uint32_t& r1, uint32_t& r2, uint32_t& r3) {
  asm volatile("ldmatrix.sync.aligned.m8n8.x4.trans.shared.b16 {%0,%1,%2,%3}, [%4];"
    : "=r"(r0), "=r"(r1), "=r"(r2), "=r"(r3) : "r"(addr) : "memory");
}
__device__ __forceinline__ void stsm_x4(uint32_t addr, uint32_t r0, uint32_t r1, uint32_t r2, uint32_t r3) {
  asm volatile("stmatrix.sync.aligned.m8n8.x4.shared.b16 [%0], {%1,%2,%3,%4};"
    :: "r"(addr), "r"(r0), "r"(r1), "r"(r2), "r"(r3) : "memory");
}
__device__ __forceinline__ void mma_16816(float& d0, float& d1, float& d2, float& d3,
                                          uint32_t a0, uint32_t a1, uint32_t a2, uint32_t a3, uint32_t b0, uint32_t b1) {
  asm volatile("mma.sync.aligned.m16n8k16.row.col.f32.bf16.bf16.f32 {%0,%1,%2,%3}, {%4,%5,%6,%7}, {%8,%9}, {%0,%1,%2,%3};"
    : "+f"(d0), "+f"(d1), "+f"(d2), "+f"(d3) : "r"(a0), "r"(a1), "r"(a2), "r"(a3), "r"(b0), "r"(b1));
}
__device__ __forceinline__ uint4 lds128(uint32_t addr) {
  uint4 v; asm volatile("ld.shared.v4.u32 {%0,%1,%2,%3}, [%4];" : "=r"(v.x), "=r"(v.y), "=r"(v.z), "=r"(v.w) : "r"(addr) : "memory");
  return v;
}

__device__ __forceinline__ void wgmma_n192_ss(float (&d)[96], uint64_t da, uint64_t db, int scale_d) {
  asm volatile("{\n.reg .pred p;\nsetp.ne.b32 p, %98, 0;\n"
    "wgmma.mma_async.sync.aligned.m64n192k16.f32.bf16.bf16 {%0, %1, %2, %3, %4, %5, %6, %7, %8, %9, %10, %11, %12, %13, %14, %15, %16, %17, %18, %19, %20, %21, %22, %23, %24, %25, %26, %27, %28, %29, %30, %31, %32, %33, %34, %35, %36, %37, %38, %39, %40, %41, %42, %43, %44, %45, %46, %47, %48, %49, %50, %51, %52, %53, %54, %55, %56, %57, %58, %59, %60, %61, %62, %63, %64, %65, %66, %67, %68, %69, %70, %71, %72, %73, %74, %75, %76, %77, %78, %79, %80, %81, %82, %83, %84, %85, %86, %87, %88, %89, %90, %91, %92, %93, %94, %95}, %96, %97, p, 1, 1, 0, 0;\n}\n"
    : "+f"(d[0]), "+f"(d[1]), "+f"(d[2]), "+f"(d[3]), "+f"(d[4]), "+f"(d[5]), "+f"(d[6]), "+f"(d[7]), "+f"(d[8]), "+f"(d[9]), "+f"(d[10]), "+f"(d[11]), "+f"(d[12]), "+f"(d[13]), "+f"(d[14]), "+f"(d[15]), "+f"(d[16]), "+f"(d[17]), "+f"(d[18]), "+f"(d[19]), "+f"(d[20]), "+f"(d[21]), "+f"(d[22]), "+f"(d[23]), "+f"(d[24]), "+f"(d[25]), "+f"(d[26]), "+f"(d[27]), "+f"(d[28]), "+f"(d[29]), "+f"(d[30]), "+f"(d[31]), "+f"(d[32]), "+f"(d[33]), "+f"(d[34]), "+f"(d[35]), "+f"(d[36]), "+f"(d[37]), "+f"(d[38]), "+f"(d[39]), "+f"(d[40]), "+f"(d[41]), "+f"(d[42]), "+f"(d[43]), "+f"(d[44]), "+f"(d[45]), "+f"(d[46]), "+f"(d[47]), "+f"(d[48]), "+f"(d[49]), "+f"(d[50]), "+f"(d[51]), "+f"(d[52]), "+f"(d[53]), "+f"(d[54]), "+f"(d[55]), "+f"(d[56]), "+f"(d[57]), "+f"(d[58]), "+f"(d[59]), "+f"(d[60]), "+f"(d[61]), "+f"(d[62]), "+f"(d[63]), "+f"(d[64]), "+f"(d[65]), "+f"(d[66]), "+f"(d[67]), "+f"(d[68]), "+f"(d[69]), "+f"(d[70]), "+f"(d[71]), "+f"(d[72]), "+f"(d[73]), "+f"(d[74]), "+f"(d[75]), "+f"(d[76]), "+f"(d[77]), "+f"(d[78]), "+f"(d[79]), "+f"(d[80]), "+f"(d[81]), "+f"(d[82]), "+f"(d[83]), "+f"(d[84]), "+f"(d[85]), "+f"(d[86]), "+f"(d[87]), "+f"(d[88]), "+f"(d[89]), "+f"(d[90]), "+f"(d[91]), "+f"(d[92]), "+f"(d[93]), "+f"(d[94]), "+f"(d[95])
    : "l"(da), "l"(db), "r"(scale_d));
}

__device__ __forceinline__ void wgmma_n192_rs(float (&d)[96], uint32_t a0, uint32_t a1, uint32_t a2, uint32_t a3, uint64_t db, int scale_d) {
  asm volatile("{\n.reg .pred p;\nsetp.ne.b32 p, %101, 0;\n"
    "wgmma.mma_async.sync.aligned.m64n192k16.f32.bf16.bf16 {%0, %1, %2, %3, %4, %5, %6, %7, %8, %9, %10, %11, %12, %13, %14, %15, %16, %17, %18, %19, %20, %21, %22, %23, %24, %25, %26, %27, %28, %29, %30, %31, %32, %33, %34, %35, %36, %37, %38, %39, %40, %41, %42, %43, %44, %45, %46, %47, %48, %49, %50, %51, %52, %53, %54, %55, %56, %57, %58, %59, %60, %61, %62, %63, %64, %65, %66, %67, %68, %69, %70, %71, %72, %73, %74, %75, %76, %77, %78, %79, %80, %81, %82, %83, %84, %85, %86, %87, %88, %89, %90, %91, %92, %93, %94, %95}, {%96, %97, %98, %99}, %100, p, 1, 1, 0;\n}\n"
    : "+f"(d[0]), "+f"(d[1]), "+f"(d[2]), "+f"(d[3]), "+f"(d[4]), "+f"(d[5]), "+f"(d[6]), "+f"(d[7]), "+f"(d[8]), "+f"(d[9]), "+f"(d[10]), "+f"(d[11]), "+f"(d[12]), "+f"(d[13]), "+f"(d[14]), "+f"(d[15]), "+f"(d[16]), "+f"(d[17]), "+f"(d[18]), "+f"(d[19]), "+f"(d[20]), "+f"(d[21]), "+f"(d[22]), "+f"(d[23]), "+f"(d[24]), "+f"(d[25]), "+f"(d[26]), "+f"(d[27]), "+f"(d[28]), "+f"(d[29]), "+f"(d[30]), "+f"(d[31]), "+f"(d[32]), "+f"(d[33]), "+f"(d[34]), "+f"(d[35]), "+f"(d[36]), "+f"(d[37]), "+f"(d[38]), "+f"(d[39]), "+f"(d[40]), "+f"(d[41]), "+f"(d[42]), "+f"(d[43]), "+f"(d[44]), "+f"(d[45]), "+f"(d[46]), "+f"(d[47]), "+f"(d[48]), "+f"(d[49]), "+f"(d[50]), "+f"(d[51]), "+f"(d[52]), "+f"(d[53]), "+f"(d[54]), "+f"(d[55]), "+f"(d[56]), "+f"(d[57]), "+f"(d[58]), "+f"(d[59]), "+f"(d[60]), "+f"(d[61]), "+f"(d[62]), "+f"(d[63]), "+f"(d[64]), "+f"(d[65]), "+f"(d[66]), "+f"(d[67]), "+f"(d[68]), "+f"(d[69]), "+f"(d[70]), "+f"(d[71]), "+f"(d[72]), "+f"(d[73]), "+f"(d[74]), "+f"(d[75]), "+f"(d[76]), "+f"(d[77]), "+f"(d[78]), "+f"(d[79]), "+f"(d[80]), "+f"(d[81]), "+f"(d[82]), "+f"(d[83]), "+f"(d[84]), "+f"(d[85]), "+f"(d[86]), "+f"(d[87]), "+f"(d[88]), "+f"(d[89]), "+f"(d[90]), "+f"(d[91]), "+f"(d[92]), "+f"(d[93]), "+f"(d[94]), "+f"(d[95])
    : "r"(a0), "r"(a1), "r"(a2), "r"(a3), "l"(db), "r"(scale_d));
}

__device__ __forceinline__ void wgmma_n192_rs_tb(float (&d)[96], uint32_t a0, uint32_t a1, uint32_t a2, uint32_t a3, uint64_t db, int scale_d) {
  asm volatile("{\n.reg .pred p;\nsetp.ne.b32 p, %101, 0;\n"
    "wgmma.mma_async.sync.aligned.m64n192k16.f32.bf16.bf16 {%0, %1, %2, %3, %4, %5, %6, %7, %8, %9, %10, %11, %12, %13, %14, %15, %16, %17, %18, %19, %20, %21, %22, %23, %24, %25, %26, %27, %28, %29, %30, %31, %32, %33, %34, %35, %36, %37, %38, %39, %40, %41, %42, %43, %44, %45, %46, %47, %48, %49, %50, %51, %52, %53, %54, %55, %56, %57, %58, %59, %60, %61, %62, %63, %64, %65, %66, %67, %68, %69, %70, %71, %72, %73, %74, %75, %76, %77, %78, %79, %80, %81, %82, %83, %84, %85, %86, %87, %88, %89, %90, %91, %92, %93, %94, %95}, {%96, %97, %98, %99}, %100, p, 1, 1, 1;\n}\n"
    : "+f"(d[0]), "+f"(d[1]), "+f"(d[2]), "+f"(d[3]), "+f"(d[4]), "+f"(d[5]), "+f"(d[6]), "+f"(d[7]), "+f"(d[8]), "+f"(d[9]), "+f"(d[10]), "+f"(d[11]), "+f"(d[12]), "+f"(d[13]), "+f"(d[14]), "+f"(d[15]), "+f"(d[16]), "+f"(d[17]), "+f"(d[18]), "+f"(d[19]), "+f"(d[20]), "+f"(d[21]), "+f"(d[22]), "+f"(d[23]), "+f"(d[24]), "+f"(d[25]), "+f"(d[26]), "+f"(d[27]), "+f"(d[28]), "+f"(d[29]), "+f"(d[30]), "+f"(d[31]), "+f"(d[32]), "+f"(d[33]), "+f"(d[34]), "+f"(d[35]), "+f"(d[36]), "+f"(d[37]), "+f"(d[38]), "+f"(d[39]), "+f"(d[40]), "+f"(d[41]), "+f"(d[42]), "+f"(d[43]), "+f"(d[44]), "+f"(d[45]), "+f"(d[46]), "+f"(d[47]), "+f"(d[48]), "+f"(d[49]), "+f"(d[50]), "+f"(d[51]), "+f"(d[52]), "+f"(d[53]), "+f"(d[54]), "+f"(d[55]), "+f"(d[56]), "+f"(d[57]), "+f"(d[58]), "+f"(d[59]), "+f"(d[60]), "+f"(d[61]), "+f"(d[62]), "+f"(d[63]), "+f"(d[64]), "+f"(d[65]), "+f"(d[66]), "+f"(d[67]), "+f"(d[68]), "+f"(d[69]), "+f"(d[70]), "+f"(d[71]), "+f"(d[72]), "+f"(d[73]), "+f"(d[74]), "+f"(d[75]), "+f"(d[76]), "+f"(d[77]), "+f"(d[78]), "+f"(d[79]), "+f"(d[80]), "+f"(d[81]), "+f"(d[82]), "+f"(d[83]), "+f"(d[84]), "+f"(d[85]), "+f"(d[86]), "+f"(d[87]), "+f"(d[88]), "+f"(d[89]), "+f"(d[90]), "+f"(d[91]), "+f"(d[92]), "+f"(d[93]), "+f"(d[94]), "+f"(d[95])
    : "r"(a0), "r"(a1), "r"(a2), "r"(a3), "l"(db), "r"(scale_d));
}

__device__ __forceinline__ void wgmma_n56_rs(float (&d)[28], uint32_t a0, uint32_t a1, uint32_t a2, uint32_t a3, uint64_t db, int scale_d) {
  asm volatile("{\n.reg .pred p;\nsetp.ne.b32 p, %33, 0;\n"
    "wgmma.mma_async.sync.aligned.m64n56k16.f32.bf16.bf16 {%0, %1, %2, %3, %4, %5, %6, %7, %8, %9, %10, %11, %12, %13, %14, %15, %16, %17, %18, %19, %20, %21, %22, %23, %24, %25, %26, %27}, {%28, %29, %30, %31}, %32, p, 1, 1, 0;\n}\n"
    : "+f"(d[0]), "+f"(d[1]), "+f"(d[2]), "+f"(d[3]), "+f"(d[4]), "+f"(d[5]), "+f"(d[6]), "+f"(d[7]), "+f"(d[8]), "+f"(d[9]), "+f"(d[10]), "+f"(d[11]), "+f"(d[12]), "+f"(d[13]), "+f"(d[14]), "+f"(d[15]), "+f"(d[16]), "+f"(d[17]), "+f"(d[18]), "+f"(d[19]), "+f"(d[20]), "+f"(d[21]), "+f"(d[22]), "+f"(d[23]), "+f"(d[24]), "+f"(d[25]), "+f"(d[26]), "+f"(d[27])
    : "r"(a0), "r"(a1), "r"(a2), "r"(a3), "l"(db), "r"(scale_d));
}

__device__ __forceinline__ void acc_fence(float (&d)[96]) {
  asm volatile("" : "+f"(d[0]), "+f"(d[1]), "+f"(d[2]), "+f"(d[3]), "+f"(d[4]), "+f"(d[5]), "+f"(d[6]), "+f"(d[7]), "+f"(d[8]), "+f"(d[9]), "+f"(d[10]), "+f"(d[11]), "+f"(d[12]), "+f"(d[13]), "+f"(d[14]), "+f"(d[15]), "+f"(d[16]), "+f"(d[17]), "+f"(d[18]), "+f"(d[19]), "+f"(d[20]), "+f"(d[21]), "+f"(d[22]), "+f"(d[23]), "+f"(d[24]), "+f"(d[25]), "+f"(d[26]), "+f"(d[27]), "+f"(d[28]), "+f"(d[29]), "+f"(d[30]), "+f"(d[31]), "+f"(d[32]), "+f"(d[33]), "+f"(d[34]), "+f"(d[35]), "+f"(d[36]), "+f"(d[37]), "+f"(d[38]), "+f"(d[39]), "+f"(d[40]), "+f"(d[41]), "+f"(d[42]), "+f"(d[43]), "+f"(d[44]), "+f"(d[45]), "+f"(d[46]), "+f"(d[47]), "+f"(d[48]), "+f"(d[49]), "+f"(d[50]), "+f"(d[51]), "+f"(d[52]), "+f"(d[53]), "+f"(d[54]), "+f"(d[55]), "+f"(d[56]), "+f"(d[57]), "+f"(d[58]), "+f"(d[59]), "+f"(d[60]), "+f"(d[61]), "+f"(d[62]), "+f"(d[63]), "+f"(d[64]), "+f"(d[65]), "+f"(d[66]), "+f"(d[67]), "+f"(d[68]), "+f"(d[69]), "+f"(d[70]), "+f"(d[71]), "+f"(d[72]), "+f"(d[73]), "+f"(d[74]), "+f"(d[75]), "+f"(d[76]), "+f"(d[77]), "+f"(d[78]), "+f"(d[79]), "+f"(d[80]), "+f"(d[81]), "+f"(d[82]), "+f"(d[83]), "+f"(d[84]), "+f"(d[85]), "+f"(d[86]), "+f"(d[87]), "+f"(d[88]), "+f"(d[89]), "+f"(d[90]), "+f"(d[91]), "+f"(d[92]), "+f"(d[93]), "+f"(d[94]), "+f"(d[95]) :: "memory");
}

__device__ __forceinline__ void acc_fence(float (&d)[28]) {
  asm volatile("" : "+f"(d[0]), "+f"(d[1]), "+f"(d[2]), "+f"(d[3]), "+f"(d[4]), "+f"(d[5]), "+f"(d[6]), "+f"(d[7]), "+f"(d[8]), "+f"(d[9]), "+f"(d[10]), "+f"(d[11]), "+f"(d[12]), "+f"(d[13]), "+f"(d[14]), "+f"(d[15]), "+f"(d[16]), "+f"(d[17]), "+f"(d[18]), "+f"(d[19]), "+f"(d[20]), "+f"(d[21]), "+f"(d[22]), "+f"(d[23]), "+f"(d[24]), "+f"(d[25]), "+f"(d[26]), "+f"(d[27]) :: "memory");
}


__global__ void __launch_bounds__(192) fold_weights_kernel(const __nv_bfloat16* __restrict__ wqkv_t, const __nv_bfloat16* __restrict__ wo_t,
                                    const __nv_bfloat16* __restrict__ wqkv_s, const __nv_bfloat16* __restrict__ wo_s) {
  __shared__ float cmA[CH];
  __shared__ float Bs[16][CH + 4];
  const int mat = blockIdx.y, n0 = blockIdx.x * 16, tid = threadIdx.x;
  const __nv_bfloat16* wqkv = (mat < 2) ? wqkv_t : wqkv_s;
  const __nv_bfloat16* wo = (mat < 2) ? wo_t : wo_s;
  const bool isM = (mat & 1) == 0;
  const int offA = isM ? 0 : 2 * CH;
  uint4 rowv[24];
  {
    const uint4* ap = reinterpret_cast<const uint4*>(wqkv + tid * 3 * CH + offA);
#pragma unroll
    for (int i = 0; i < 24; i++) rowv[i] = ap[i];
    float s[8] = {0.f, 0.f, 0.f, 0.f, 0.f, 0.f, 0.f, 0.f}, s2[8] = {0.f, 0.f, 0.f, 0.f, 0.f, 0.f, 0.f, 0.f};
#pragma unroll 3
    for (int a = 0; a < CH; a += 8) {
#pragma unroll
      for (int i = 0; i < 8; i++) {
        s[i] += __bfloat162float(wqkv[(a + i) * 3 * CH + offA + tid]);
        if (isM) s2[i] += __bfloat162float(wqkv[(a + i) * 3 * CH + CH + tid]);
      }
    }
    cmA[tid] = (((s[0] + s[1]) + (s[2] + s[3])) + ((s[4] + s[5]) + (s[6] + s[7]))) * (1.0f / CH);
    const float cmB = (((s2[0] + s2[1]) + (s2[2] + s2[3])) + ((s2[4] + s2[5]) + (s2[6] + s2[7]))) * (1.0f / CH);
#pragma unroll
    for (int n = 0; n < 16; n++) {
      Bs[n][tid] = isM ? (__bfloat162float(wqkv[(n0 + n) * 3 * CH + CH + tid]) - cmB)
                       : __bfloat162float(wo[tid * CH + n0 + n]);
    }
  }
  __syncthreads();
  float acc[16];
#pragma unroll
  for (int n = 0; n < 16; n++) acc[n] = 0.f;
#pragma unroll
  for (int c8 = 0; c8 < 24; c8++) {
    const uint32_t u[4] = {rowv[c8].x, rowv[c8].y, rowv[c8].z, rowv[c8].w};
#pragma unroll
    for (int hh = 0; hh < 2; hh++) {
      const int c = c8 * 8 + hh * 4;
      float a[4];
      a[0] = bf_lo(u[hh * 2]) - cmA[c]; a[1] = bf_hi(u[hh * 2]) - cmA[c + 1];
      a[2] = bf_lo(u[hh * 2 + 1]) - cmA[c + 2]; a[3] = bf_hi(u[hh * 2 + 1]) - cmA[c + 3];
#pragma unroll
      for (int n = 0; n < 16; n++) {
        const float4 b = *reinterpret_cast<const float4*>(&Bs[n][c]);
        acc[n] = fmaf(a[0], b.x, acc[n]); acc[n] = fmaf(a[1], b.y, acc[n]);
        acc[n] = fmaf(a[2], b.z, acc[n]); acc[n] = fmaf(a[3], b.w, acc[n]);
      }
    }
  }
  const int k = tid, p = k >> 6, kc = k & 63;
#pragma unroll
  for (int n = 0; n < 16; n++) {
    const int nn = n0 + n;
    g_w[mat][p * (CH * 64) + nn * 64 + (((kc >> 3) ^ (nn & 7)) << 3) + (kc & 7)] = __float2bfloat16(acc[n]);
  }
}

struct Params {
  int role;
};

__device__ __forceinline__ uint32_t frag_addr(uint32_t slot_rowoff, uint32_t sw, int hiblk, int kk) {
  const int ci = 2 * kk + hiblk;
  return slot_rowoff + (ci >> 3) * PANEL_X + ((((uint32_t)ci & 7u) ^ sw) << 4);
}

__device__ __forceinline__ float row_rstd(uint32_t slot, int w, int lane) {
  const int row = 16 * w + (lane >> 1), half = lane & 1;
  const uint32_t rbase = slot + row * 128, sw = row & 7;
  float s = 0.f, ss = 0.f;
#pragma unroll
  for (int i = 0; i < 12; i++) {
    const int c = half * 12 + i;
    const uint4 v = lds128(rbase + (c >> 3) * PANEL_X + ((((uint32_t)c & 7u) ^ sw) << 4));
    const uint32_t u[4] = {v.x, v.y, v.z, v.w};
#pragma unroll
    for (int e = 0; e < 4; e++) {
      const float lo = bf_lo(u[e]), hi = bf_hi(u[e]);
      s += lo; s += hi;
      ss = fmaf(lo, lo, ss); ss = fmaf(hi, hi, ss);
    }
  }
  s += __shfl_xor_sync(0xffffffffu, s, 1);
  ss += __shfl_xor_sync(0xffffffffu, ss, 1);
  const float mean = s * (1.0f / CH);
  const float var = fmaxf(ss * (1.0f / CH) - mean * mean, 0.f);
  return rsqrtf(var + 1e-5f);
}

__global__ void __launch_bounds__(NWG * 128, 1)
swin_main_kernel(const __grid_constant__ CUtensorMap map_in, const __grid_constant__ CUtensorMap map_out, const int role) {
  extern __shared__ __align__(1024) uint8_t smem_raw[];
  const uint32_t sbase = smem_u32(smem_raw);
  const int tid = threadIdx.x, wg = tid >> 7, t128 = tid & 127, w = t128 >> 5, lane = tid & 31;
  const int g = lane >> 2, q = lane & 3;

  const uint32_t bar_w = sbase + SMEM_MISC;
  float* rbuf = reinterpret_cast<float*>(smem_raw + SMEM_RBUF) + wg * 64;

  if (tid == 0) {
    mbar_init(bar_w, 1);
    for (int i = 0; i < NSLOT; i++) mbar_init(sbase + SMEM_MISC + 8 + 8 * i, 1);
    asm volatile("fence.mbarrier_init.release.cluster;" ::: "memory");
  }
  for (int i = tid; i < NSLOT * SLOT_BYTES / 16; i += NWG * 128)
    *reinterpret_cast<uint4*>(smem_raw + SMEM_SLOT + i * 16) = make_uint4(0, 0, 0, 0);
  fence_proxy_async();
  __syncthreads();

  const int nunits = role == 0 ? NTILE_A : NUNIT_B;
  const int ustride = gridDim.x;
  const int nj = (nunits - (int)blockIdx.x + ustride - 1) / ustride;
  const uint32_t tx_bytes = role == 0 ? SLOT_BYTES : 3 * 49 * 128;

  auto coords = [&](int j, int& c1, int& c2, int& c3) {
    const int u = blockIdx.x + j * ustride;
    if (role == 0) { c1 = 0; c2 = (u % 14) * 16; c3 = u / 14; }
    else { const int t = u & 3, wx = (u >> 2) & 31, wy = u >> 7; c1 = wx * 7; c2 = wy * 7; c3 = t; }
  };
  auto issue_load = [&](int j) {
    int c1, c2, c3; coords(j, c1, c2, c3);
    const int sl = j % NSLOT;
    const uint32_t bar = sbase + SMEM_MISC + 8 + 8 * sl;
    mbar_expect_tx(bar, tx_bytes);
#pragma unroll
    for (int p = 0; p < 3; p++) tma_load_4d(sbase + SMEM_SLOT + sl * SLOT_BYTES + p * PANEL_X, &map_in, p * 64, c1, c2, c3, bar);
  };
  auto prefetch_l2 = [&](int j) {
    if (j < nj) {
      int c1, c2, c3; coords(j, c1, c2, c3);
#pragma unroll
      for (int p = 0; p < 3; p++) tma_prefetch_4d(&map_in, p * 64, c1, c2, c3);
    }
  };

  if (tid == 0) {
    mbar_expect_tx(bar_w, 2 * WMAT_BYTES);
    bulk_load(sbase + SMEM_W0, &g_w[role * 2][0], WMAT_BYTES, bar_w);
    bulk_load(sbase + SMEM_W1, &g_w[role * 2 + 1][0], WMAT_BYTES, bar_w);
    for (int j = 0; j < NSLOT && j < nj; j++) issue_load(j);
    prefetch_l2(NSLOT); prefetch_l2(NSLOT + 1);
  }
  __syncwarp();
  mbar_wait(bar_w, 0);

  const int blk = lane >> 3;
  const int frow = 16 * w + (lane & 7) + ((blk & 1) << 3);
  const uint32_t fsw = frow & 7;
  const int fhi = blk >> 1;

  const uint64_t dW0 = make_desc(sbase + SMEM_W0, 16, 1024);
  const uint64_t dW1 = make_desc(sbase + SMEM_W1, 16, 1024);

  const float scale_l2e = 0.07216878364870322f * 1.4426950408889634f;

  for (int j = wg; j < nj; j += NWG) {
    const int sl = j % NSLOT;
    const uint32_t slot = sbase + SMEM_SLOT + sl * SLOT_BYTES;
    const uint32_t frowoff = slot + frow * 128;
    const uint64_t dX = make_desc(slot, 16, 1024);
    const uint64_t dXmn = make_desc(slot, PANEL_X, 1024);
    mbar_wait(sbase + SMEM_MISC + 8 + 8 * sl, (j / NSLOT) & 1);

    float acc[96];
    wgmma_fence();
#pragma unroll
    for (int kk = 0; kk < 12; kk++) {
      const uint32_t off = (kk >> 2) * PANEL_X + (kk & 3) * 32;
      const uint32_t offw = (kk >> 2) * PANEL_W + (kk & 3) * 32;
      wgmma_n192_ss(acc, dX + (off >> 4), dW0 + (offw >> 4), kk);
    }
    wgmma_commit();
    const float rmine = row_rstd(slot, w, lane);
    uint32_t fr[48];

    if (role == 0) {
      wgmma_wait0(); acc_fence(acc);
#pragma unroll
      for (int i = 0; i < 48; i++) fr[i] = pack_bf16(acc[2 * i], acc[2 * i + 1]);
      float d0[4] = {0.f, 0.f, 0.f, 0.f}, d1[4] = {0.f, 0.f, 0.f, 0.f};
#pragma unroll
      for (int kk = 0; kk < 12; kk++) {
        uint32_t b0, b1, b2, b3;
        ldsm_x4(frag_addr(frowoff, fsw, fhi, kk), b0, b1, b2, b3);
        mma_16816(d0[0], d0[1], d0[2], d0[3], fr[4 * kk], fr[4 * kk + 1], fr[4 * kk + 2], fr[4 * kk + 3], b0, b2);
        mma_16816(d1[0], d1[1], d1[2], d1[3], fr[4 * kk], fr[4 * kk + 1], fr[4 * kk + 2], fr[4 * kk + 3], b1, b3);
      }
      const float rA = __shfl_sync(0xffffffffu, rmine, 2 * g);
      const float rB = __shfl_sync(0xffffffffu, rmine, 2 * g + 16);
      const float k0 = __shfl_sync(0xffffffffu, rmine, 4 * q);
      const float k1 = __shfl_sync(0xffffffffu, rmine, 4 * q + 2);
      const float k2 = __shfl_sync(0xffffffffu, rmine, 4 * q + 16);
      const float k3 = __shfl_sync(0xffffffffu, rmine, 4 * q + 18);
      const bool valid = (g >> 2) == (q >> 1);
      float sa0 = d0[0] * k0 * (rA * scale_l2e), sa1 = d0[1] * k1 * (rA * scale_l2e);
      float sb0 = d1[2] * k2 * (rB * scale_l2e), sb1 = d1[3] * k3 * (rB * scale_l2e);
      float ma = fmaxf(sa0, sa1), mb = fmaxf(sb0, sb1);
      ma = fmaxf(ma, __shfl_xor_sync(0xffffffffu, ma, 1));
      mb = fmaxf(mb, __shfl_xor_sync(0xffffffffu, mb, 1));
      const float ea0 = exp2f(sa0 - ma), ea1 = exp2f(sa1 - ma);
      const float eb0 = exp2f(sb0 - mb), eb1 = exp2f(sb1 - mb);
      float suma = ea0 + ea1, sumb = eb0 + eb1;
      suma += __shfl_xor_sync(0xffffffffu, suma, 1);
      sumb += __shfl_xor_sync(0xffffffffu, sumb, 1);
      const float ia = __fdividef(1.f, suma), ib = __fdividef(1.f, sumb);
      const uint32_t pa0 = valid ? pack_bf16(ea0 * ia * k0, ea1 * ia * k1) : 0u;
      const uint32_t pa3 = valid ? pack_bf16(eb0 * ib * k2, eb1 * ib * k3) : 0u;
#pragma unroll
      for (int jj = 0; jj < 12; jj++) {
        uint32_t b0, b1, b2, b3;
        ldsm_x4_t(frag_addr(frowoff, fsw, fhi, jj), b0, b1, b2, b3);
        acc[8 * jj + 0] = 0.f; acc[8 * jj + 1] = 0.f; acc[8 * jj + 2] = 0.f; acc[8 * jj + 3] = 0.f;
        acc[8 * jj + 4] = 0.f; acc[8 * jj + 5] = 0.f; acc[8 * jj + 6] = 0.f; acc[8 * jj + 7] = 0.f;
        mma_16816(acc[8 * jj + 0], acc[8 * jj + 1], acc[8 * jj + 2], acc[8 * jj + 3], pa0, 0u, 0u, pa3, b0, b1);
        mma_16816(acc[8 * jj + 4], acc[8 * jj + 5], acc[8 * jj + 6], acc[8 * jj + 7], pa0, 0u, 0u, pa3, b2, b3);
      }
    } else {
      if ((lane & 1) == 0) rbuf[16 * w + (lane >> 1)] = rmine;
      wg_bar(1 + wg);
      wgmma_wait0(); acc_fence(acc);
#pragma unroll
      for (int i = 0; i < 48; i++) fr[i] = pack_bf16(acc[2 * i], acc[2 * i + 1]);
      float s[28];
      wgmma_fence();
#pragma unroll
      for (int kk = 0; kk < 12; kk++) {
        const uint32_t off = (kk >> 2) * PANEL_X + (kk & 3) * 32;
        wgmma_n56_rs(s, fr[4 * kk], fr[4 * kk + 1], fr[4 * kk + 2], fr[4 * kk + 3], dX + (off >> 4), kk);
      }
      wgmma_commit();
      float rj[14];
#pragma unroll
      for (int j = 0; j < 7; j++) {
        const float2 v = *reinterpret_cast<const float2*>(&rbuf[8 * j + 2 * q]);
        rj[2 * j] = v.x; rj[2 * j + 1] = v.y;
      }
      const float ri0 = rbuf[16 * w + g] * scale_l2e, ri1 = rbuf[16 * w + g + 8] * scale_l2e;
      wgmma_wait0(); acc_fence(s);
      float m0 = -INFINITY, m1 = -INFINITY;
#pragma unroll
      for (int j = 0; j < 7; j++) {
#pragma unroll
        for (int e = 0; e < 2; e++) {
          const bool ok = (j < 6) || (2 * q + e == 0);
          float v0 = s[4 * j + e] * rj[2 * j + e] * ri0;
          float v1 = s[4 * j + 2 + e] * rj[2 * j + e] * ri1;
          v0 = ok ? v0 : -INFINITY; v1 = ok ? v1 : -INFINITY;
          s[4 * j + e] = v0; s[4 * j + 2 + e] = v1;
          m0 = fmaxf(m0, v0); m1 = fmaxf(m1, v1);
        }
      }
      m0 = fmaxf(m0, __shfl_xor_sync(0xffffffffu, m0, 1)); m0 = fmaxf(m0, __shfl_xor_sync(0xffffffffu, m0, 2));
      m1 = fmaxf(m1, __shfl_xor_sync(0xffffffffu, m1, 1)); m1 = fmaxf(m1, __shfl_xor_sync(0xffffffffu, m1, 2));
      float sum0 = 0.f, sum1 = 0.f;
#pragma unroll
      for (int j = 0; j < 7; j++) {
#pragma unroll
        for (int e = 0; e < 2; e++) {
          const float e0 = exp2f(s[4 * j + e] - m0), e1 = exp2f(s[4 * j + 2 + e] - m1);
          s[4 * j + e] = e0; s[4 * j + 2 + e] = e1;
          sum0 += e0; sum1 += e1;
        }
      }
      sum0 += __shfl_xor_sync(0xffffffffu, sum0, 1); sum0 += __shfl_xor_sync(0xffffffffu, sum0, 2);
      sum1 += __shfl_xor_sync(0xffffffffu, sum1, 1); sum1 += __shfl_xor_sync(0xffffffffu, sum1, 2);
      const float i0 = __fdividef(1.f, sum0), i1 = __fdividef(1.f, sum1);
      uint32_t pa[16];
#pragma unroll
      for (int j = 0; j < 7; j++) {
        pa[(j >> 1) * 4 + (j & 1) * 2 + 0] = pack_bf16(s[4 * j] * i0 * rj[2 * j], s[4 * j + 1] * i0 * rj[2 * j + 1]);
        pa[(j >> 1) * 4 + (j & 1) * 2 + 1] = pack_bf16(s[4 * j + 2] * i1 * rj[2 * j], s[4 * j + 3] * i1 * rj[2 * j + 1]);
      }
      pa[14] = 0u; pa[15] = 0u;
      wgmma_fence();
#pragma unroll
      for (int kk = 0; kk < 4; kk++)
        wgmma_n192_rs_tb(acc, pa[4 * kk], pa[4 * kk + 1], pa[4 * kk + 2], pa[4 * kk + 3], dXmn + ((kk * 2048) >> 4), kk);
      wgmma_commit();
      wgmma_wait0(); acc_fence(acc);
    }

#pragma unroll
    for (int i = 0; i < 48; i++) fr[i] = pack_bf16(acc[2 * i], acc[2 * i + 1]);
    wgmma_fence();
#pragma unroll
    for (int kk = 0; kk < 12; kk++) {
      const uint32_t offw = (kk >> 2) * PANEL_W + (kk & 3) * 32;
      wgmma_n192_rs(acc, fr[4 * kk], fr[4 * kk + 1], fr[4 * kk + 2], fr[4 * kk + 3], dW1 + (offw >> 4), kk);
    }
    wgmma_commit();
    wgmma_wait0(); acc_fence(acc);
    wg_bar(1 + wg);
#pragma unroll
    for (int kk = 0; kk < 12; kk++) {
      const uint32_t a = frag_addr(frowoff, fsw, fhi, kk);
      uint32_t x0, x1, x2, x3;
      ldsm_x4(a, x0, x1, x2, x3);
      const uint32_t o0 = pack_bf16(acc[8 * kk + 0] + bf_lo(x0), acc[8 * kk + 1] + bf_hi(x0));
      const uint32_t o1 = pack_bf16(acc[8 * kk + 2] + bf_lo(x1), acc[8 * kk + 3] + bf_hi(x1));
      const uint32_t o2 = pack_bf16(acc[8 * kk + 4] + bf_lo(x2), acc[8 * kk + 5] + bf_hi(x2));
      const uint32_t o3 = pack_bf16(acc[8 * kk + 6] + bf_lo(x3), acc[8 * kk + 7] + bf_hi(x3));
      stsm_x4(a, o0, o1, o2, o3);
    }
    fence_proxy_async();
    wg_bar(1 + wg);
    if (t128 == 0) {
      int c1, c2, c3; coords(j, c1, c2, c3);
#pragma unroll
      for (int p = 0; p < 3; p++) tma_store_4d(&map_out, slot + p * PANEL_X, p * 64, c1, c2, c3);
      bulk_commit();
      bulk_wait_read0();
      if (j + NSLOT < nj) issue_load(j + NSLOT);
      prefetch_l2(j + NSLOT + 2);
    }
    __syncwarp();
  }
  if (t128 == 0) bulk_wait0();
}

typedef CUresult (*EncodeTiledFn)(CUtensorMap*, CUtensorMapDataType, cuuint32_t, void*, const cuuint64_t*, const cuuint64_t*,
                                  const cuuint32_t*, const cuuint32_t*, CUtensorMapInterleave, CUtensorMapSwizzle,
                                  CUtensorMapL2promotion, CUtensorMapFloatOOBfill);

bool make_map(EncodeTiledFn fn, CUtensorMap* m, void* base, bool pixel_major) {
  cuuint64_t dims[4]; cuuint64_t strides[3]; cuuint32_t box[4]; cuuint32_t es[4] = {1, 1, 1, 1};
  const cuuint64_t sC = (cuuint64_t)CH * 2, sW = sC * WW, sT = sW * HH;
  if (pixel_major) {
    dims[0] = CH; dims[1] = TT; dims[2] = WW; dims[3] = HH;
    strides[0] = sT; strides[1] = sC; strides[2] = sW;
    box[0] = 64; box[1] = 4; box[2] = 16; box[3] = 1;
  } else {
    dims[0] = CH; dims[1] = WW; dims[2] = HH; dims[3] = TT;
    strides[0] = sC; strides[1] = sW; strides[2] = sT;
    box[0] = 64; box[1] = 7; box[2] = 7; box[3] = 1;
  }
  return fn(m, CU_TENSOR_MAP_DATA_TYPE_BFLOAT16, 4, base, dims, strides, box, es, CU_TENSOR_MAP_INTERLEAVE_NONE,
            CU_TENSOR_MAP_SWIZZLE_128B, CU_TENSOR_MAP_L2_PROMOTION_L2_256B, CU_TENSOR_MAP_FLOAT_OOB_FILL_NONE) == CUDA_SUCCESS;
}

}

extern "C" void kernel_launch(void* const* d_in, const int* in_sizes, int n_in, void* d_out, int out_size) {
  const __nv_bfloat16* x = (const __nv_bfloat16*)d_in[0];
  const __nv_bfloat16* wqkv_t = (const __nv_bfloat16*)d_in[1];
  const __nv_bfloat16* wo_t = (const __nv_bfloat16*)d_in[2];
  const __nv_bfloat16* wqkv_s = (const __nv_bfloat16*)d_in[3];
  const __nv_bfloat16* wo_s = (const __nv_bfloat16*)d_in[4];

  static bool init = false;
  static CUtensorMap mA_in, mA_out, mB_in, mB_out;
  static void* last_x = nullptr; static void* last_out = nullptr;
  static int nsm = 132;
  if (!init || last_x != d_in[0] || last_out != d_out) {
    void* fnp = nullptr; cudaDriverEntryPointQueryResult qr;
    cudaGetDriverEntryPoint("cuTensorMapEncodeTiled", &fnp, cudaEnableDefault, &qr);
    EncodeTiledFn fn = (EncodeTiledFn)fnp;
    void* x1p = nullptr; cudaGetSymbolAddress(&x1p, g_x1);
    make_map(fn, &mA_in, (void*)x, true);
    make_map(fn, &mA_out, x1p, true);
    make_map(fn, &mB_in, x1p, false);
    make_map(fn, &mB_out, d_out, false);
    cudaFuncSetAttribute(swin_main_kernel, cudaFuncAttributeMaxDynamicSharedMemorySize, SMEM_TOTAL);
    cudaDeviceGetAttribute(&nsm, cudaDevAttrMultiProcessorCount, 0);
    init = true; last_x = d_in[0]; last_out = d_out;
  }
  fold_weights_kernel<<<dim3(12, 4), 192>>>(wqkv_t, wo_t, wqkv_s, wo_s);
  swin_main_kernel<<<nsm, NWG * 128, SMEM_TOTAL>>>(mA_in, mA_out, 0);
  swin_main_kernel<<<nsm, NWG * 128, SMEM_TOTAL>>>(mB_in, mB_out, 1);
}
```

```cpp
#include <cuda_runtime.h>
#include <cuda_bf16.h>
#include <cuda.h>
#include <stdint.h>

namespace {

constexpr int CH = 192;
constexpr int TT = 4, HH = 224, WW = 224;
constexpr int NTOK = TT * HH * WW;
constexpr int PANEL_X = 64 * 128;
constexpr int SLOT_BYTES = 3 * PANEL_X;
constexpr int PANEL_W = 192 * 128;
constexpr int WMAT_BYTES = 3 * PANEL_W;
constexpr int NWG = 2;
constexpr int NSLOT = 3;
constexpr int SMEM_W0 = 0;
constexpr int SMEM_W1 = WMAT_BYTES;
constexpr int SMEM_SLOT = 2 * WMAT_BYTES;
constexpr int SMEM_MISC = SMEM_SLOT + NSLOT * SLOT_BYTES;
constexpr int SMEM_RBUF = SMEM_MISC + 128;
constexpr int SMEM_TOTAL = SMEM_RBUF + NWG * 64 * 4;

constexpr int NTILE_A = HH * (WW / 16);
constexpr int NUNIT_B = 32 * 32 * 4;

__device__ __nv_bfloat16 g_x1[(size_t)NTOK * CH];
__device__ __align__(1024) __nv_bfloat16 g_w[4][CH * CH];

#define PH(i) do {} while (0)
__device__ __forceinline__ uint32_t smem_u32(const void* p) { return (uint32_t)__cvta_generic_to_shared(p); }

__device__ __forceinline__ void mbar_init(uint32_t bar, uint32_t count) {
  asm volatile("mbarrier.init.shared::cta.b64 [%0], %1;" :: "r"(bar), "r"(count));
}
__device__ __forceinline__ void mbar_expect_tx(uint32_t bar, uint32_t bytes) {
  asm volatile("mbarrier.arrive.expect_tx.shared::cta.b64 _, [%0], %1;" :: "r"(bar), "r"(bytes) : "memory");
}
__device__ __forceinline__ void mbar_arrive(uint32_t bar) {
  asm volatile("mbarrier.arrive.shared::cta.b64 _, [%0];" :: "r"(bar) : "memory");
}
__device__ __forceinline__ void mbar_wait(uint32_t bar, uint32_t parity) {
  asm volatile(
    "{\n.reg .pred p;\n"
    "WAIT_%=:\n"
    "mbarrier.try_wait.parity.shared::cta.b64 p, [%0], %1;\n"
    "@p bra DONE_%=;\n"
    "bra WAIT_%=;\n"
    "DONE_%=:\n}\n" :: "r"(bar), "r"(parity) : "memory");
}
__device__ __forceinline__ void tma_load_4d(uint32_t dst, const CUtensorMap* map, int c0, int c1, int c2, int c3, uint32_t bar) {
  asm volatile("cp.async.bulk.tensor.4d.shared::cluster.global.tile.mbarrier::complete_tx::bytes [%0], [%1, {%2, %3, %4, %5}], [%6];"
    :: "r"(dst), "l"(map), "r"(c0), "r"(c1), "r"(c2), "r"(c3), "r"(bar) : "memory");
}
__device__ __forceinline__ void tma_prefetch_4d(const CUtensorMap* map, int c0, int c1, int c2, int c3) {
  asm volatile("cp.async.bulk.prefetch.tensor.4d.L2.global.tile [%0, {%1, %2, %3, %4}];"
    :: "l"(map), "r"(c0), "r"(c1), "r"(c2), "r"(c3) : "memory");
}
__device__ __forceinline__ void tma_store_4d(const CUtensorMap* map, uint32_t src, int c0, int c1, int c2, int c3) {
  asm volatile("cp.async.bulk.tensor.4d.global.shared::cta.tile.bulk_group [%0, {%1, %2, %3, %4}], [%5];"
    :: "l"(map), "r"(c0), "r"(c1), "r"(c2), "r"(c3), "r"(src) : "memory");
}
__device__ __forceinline__ void bulk_load(uint32_t dst, const void* src, uint32_t bytes, uint32_t bar) {
  asm volatile("cp.async.bulk.shared::cluster.global.mbarrier::complete_tx::bytes [%0], [%1], %2, [%3];"
    :: "r"(dst), "l"(src), "r"(bytes), "r"(bar) : "memory");
}
__device__ __forceinline__ void bulk_commit() { asm volatile("cp.async.bulk.commit_group;" ::: "memory"); }
__device__ __forceinline__ void bulk_wait_read0() { asm volatile("cp.async.bulk.wait_group.read 0;" ::: "memory"); }
__device__ __forceinline__ void bulk_wait0() { asm volatile("cp.async.bulk.wait_group 0;" ::: "memory"); }
__device__ __forceinline__ void fence_proxy_async() { asm volatile("fence.proxy.async.shared::cta;" ::: "memory"); }
__device__ __forceinline__ void wg_bar(int id) { asm volatile("bar.sync %0, 128;" :: "r"(id) : "memory"); }
__device__ __forceinline__ void wgmma_fence() { asm volatile("wgmma.fence.sync.aligned;" ::: "memory"); }
__device__ __forceinline__ void wgmma_commit() { asm volatile("wgmma.commit_group.sync.aligned;" ::: "memory"); }
__device__ __forceinline__ void wgmma_wait0() { asm volatile("wgmma.wait_group.sync.aligned 0;" ::: "memory"); }

__device__ __forceinline__ uint64_t make_desc(uint32_t saddr, uint32_t lbo, uint32_t sbo) {
  return (uint64_t)((saddr & 0x3FFFF) >> 4) | ((uint64_t)((lbo & 0x3FFFF) >> 4) << 16) |
         ((uint64_t)((sbo & 0x3FFFF) >> 4) << 32) | ((uint64_t)1 << 62);
}
__device__ __forceinline__ uint32_t pack_bf16(float lo, float hi) {
  uint32_t r; asm("cvt.rn.bf16x2.f32 %0, %1, %2;" : "=r"(r) : "f"(hi), "f"(lo)); return r;
}
__device__ __forceinline__ uint32_t add_bf16x2(uint32_t a, uint32_t b) {
  uint32_t r; asm("add.rn.bf16x2 %0, %1, %2;" : "=r"(r) : "r"(a), "r"(b)); return r;
}
__device__ __forceinline__ float bf_lo(uint32_t u) { return __uint_as_float(u << 16); }
__device__ __forceinline__ float bf_hi(uint32_t u) { return __uint_as_float(u & 0xffff0000u); }
__device__ __forceinline__ void ldsm_x4(uint32_t addr, uint32_t& r0, uint32_t& r1, uint32_t& r2, uint32_t& r3) {
  asm volatile("ldmatrix.sync.aligned.m8n8.x4.shared.b16 {%0,%1,%2,%3}, [%4];"
    : "=r"(r0), "=r"(r1), "=r"(r2), "=r"(r3) : "r"(addr) : "memory");
}
__device__ __forceinline__ void ldsm_x4_t(uint32_t addr, uint32_t& r0, uint32_t& r1, uint32_t& r2, uint32_t& r3) {
  asm volatile("ldmatrix.sync.aligned.m8n8.x4.trans.shared.b16 {%0,%1,%2,%3}, [%4];"
    : "=r"(r0), "=r"(r1), "=r"(r2), "=r"(r3) : "r"(addr) : "memory");
}
__device__ __forceinline__ void stsm_x4(uint32_t addr, uint32_t r0, uint32_t r1, uint32_t r2, uint32_t r3) {
  asm volatile("stmatrix.sync.aligned.m8n8.x4.shared.b16 [%0], {%1,%2,%3,%4};"
    :: "r"(addr), "r"(r0), "r"(r1), "r"(r2), "r"(r3) : "memory");
}
__device__ __forceinline__ void mma_16816(float& d0, float& d1, float& d2, float& d3,
                                          uint32_t a0, uint32_t a1, uint32_t a2, uint32_t a3, uint32_t b0, uint32_t b1) {
  asm volatile("mma.sync.aligned.m16n8k16.row.col.f32.bf16.bf16.f32 {%0,%1,%2,%3}, {%4,%5,%6,%7}, {%8,%9}, {%0,%1,%2,%3};"
    : "+f"(d0), "+f"(d1), "+f"(d2), "+f"(d3) : "r"(a0), "r"(a1), "r"(a2), "r"(a3), "r"(b0), "r"(b1));
}
__device__ __forceinline__ uint4 lds128(uint32_t addr) {
  uint4 v; asm volatile("ld.shared.v4.u32 {%0,%1,%2,%3}, [%4];" : "=r"(v.x), "=r"(v.y), "=r"(v.z), "=r"(v.w) : "r"(addr) : "memory");
  return v;
}

__device__ __forceinline__ void wgmma_n192_ss(float (&d)[96], uint64_t da, uint64_t db, int scale_d) {
  asm volatile("{\n.reg .pred p;\nsetp.ne.b32 p, %98, 0;\n"
    "wgmma.mma_async.sync.aligned.m64n192k16.f32.bf16.bf16 {%0, %1, %2, %3, %4, %5, %6, %7, %8, %9, %10, %11, %12, %13, %14, %15, %16, %17, %18, %19, %20, %21, %22, %23, %24, %25, %26, %27, %28, %29, %30, %31, %32, %33, %34, %35, %36, %37, %38, %39, %40, %41, %42, %43, %44, %45, %46, %47, %48, %49, %50, %51, %52, %53, %54, %55, %56, %57, %58, %59, %60, %61, %62, %63, %64, %65, %66, %67, %68, %69, %70, %71, %72, %73, %74, %75, %76, %77, %78, %79, %80, %81, %82, %83, %84, %85, %86, %87, %88, %89, %90, %91, %92, %93, %94, %95}, %96, %97, p, 1, 1, 0, 0;\n}\n"
    : "+f"(d[0]), "+f"(d[1]), "+f"(d[2]), "+f"(d[3]), "+f"(d[4]), "+f"(d[5]), "+f"(d[6]), "+f"(d[7]), "+f"(d[8]), "+f"(d[9]), "+f"(d[10]), "+f"(d[11]), "+f"(d[12]), "+f"(d[13]), "+f"(d[14]), "+f"(d[15]), "+f"(d[16]), "+f"(d[17]), "+f"(d[18]), "+f"(d[19]), "+f"(d[20]), "+f"(d[21]), "+f"(d[22]), "+f"(d[23]), "+f"(d[24]), "+f"(d[25]), "+f"(d[26]), "+f"(d[27]), "+f"(d[28]), "+f"(d[29]), "+f"(d[30]), "+f"(d[31]), "+f"(d[32]), "+f"(d[33]), "+f"(d[34]), "+f"(d[35]), "+f"(d[36]), "+f"(d[37]), "+f"(d[38]), "+f"(d[39]), "+f"(d[40]), "+f"(d[41]), "+f"(d[42]), "+f"(d[43]), "+f"(d[44]), "+f"(d[45]), "+f"(d[46]), "+f"(d[47]), "+f"(d[48]), "+f"(d[49]), "+f"(d[50]), "+f"(d[51]), "+f"(d[52]), "+f"(d[53]), "+f"(d[54]), "+f"(d[55]), "+f"(d[56]), "+f"(d[57]), "+f"(d[58]), "+f"(d[59]), "+f"(d[60]), "+f"(d[61]), "+f"(d[62]), "+f"(d[63]), "+f"(d[64]), "+f"(d[65]), "+f"(d[66]), "+f"(d[67]), "+f"(d[68]), "+f"(d[69]), "+f"(d[70]), "+f"(d[71]), "+f"(d[72]), "+f"(d[73]), "+f"(d[74]), "+f"(d[75]), "+f"(d[76]), "+f"(d[77]), "+f"(d[78]), "+f"(d[79]), "+f"(d[80]), "+f"(d[81]), "+f"(d[82]), "+f"(d[83]), "+f"(d[84]), "+f"(d[85]), "+f"(d[86]), "+f"(d[87]), "+f"(d[88]), "+f"(d[89]), "+f"(d[90]), "+f"(d[91]), "+f"(d[92]), "+f"(d[93]), "+f"(d[94]), "+f"(d[95])
    : "l"(da), "l"(db), "r"(scale_d));
}

__device__ __forceinline__ void wgmma_n192_rs(float (&d)[96], uint32_t a0, uint32_t a1, uint32_t a2, uint32_t a3, uint64_t db, int scale_d) {
  asm volatile("{\n.reg .pred p;\nsetp.ne.b32 p, %101, 0;\n"
    "wgmma.mma_async.sync.aligned.m64n192k16.f32.bf16.bf16 {%0, %1, %2, %3, %4, %5, %6, %7, %8, %9, %10, %11, %12, %13, %14, %15, %16, %17, %18, %19, %20, %21, %22, %23, %24, %25, %26, %27, %28, %29, %30, %31, %32, %33, %34, %35, %36, %37, %38, %39, %40, %41, %42, %43, %44, %45, %46, %47, %48, %49, %50, %51, %52, %53, %54, %55, %56, %57, %58, %59, %60, %61, %62, %63, %64, %65, %66, %67, %68, %69, %70, %71, %72, %73, %74, %75, %76, %77, %78, %79, %80, %81, %82, %83, %84, %85, %86, %87, %88, %89, %90, %91, %92, %93, %94, %95}, {%96, %97, %98, %99}, %100, p, 1, 1, 0;\n}\n"
    : "+f"(d[0]), "+f"(d[1]), "+f"(d[2]), "+f"(d[3]), "+f"(d[4]), "+f"(d[5]), "+f"(d[6]), "+f"(d[7]), "+f"(d[8]), "+f"(d[9]), "+f"(d[10]), "+f"(d[11]), "+f"(d[12]), "+f"(d[13]), "+f"(d[14]), "+f"(d[15]), "+f"(d[16]), "+f"(d[17]), "+f"(d[18]), "+f"(d[19]), "+f"(d[20]), "+f"(d[21]), "+f"(d[22]), "+f"(d[23]), "+f"(d[24]), "+f"(d[25]), "+f"(d[26]), "+f"(d[27]), "+f"(d[28]), "+f"(d[29]), "+f"(d[30]), "+f"(d[31]), "+f"(d[32]), "+f"(d[33]), "+f"(d[34]), "+f"(d[35]), "+f"(d[36]), "+f"(d[37]), "+f"(d[38]), "+f"(d[39]), "+f"(d[40]), "+f"(d[41]), "+f"(d[42]), "+f"(d[43]), "+f"(d[44]), "+f"(d[45]), "+f"(d[46]), "+f"(d[47]), "+f"(d[48]), "+f"(d[49]), "+f"(d[50]), "+f"(d[51]), "+f"(d[52]), "+f"(d[53]), "+f"(d[54]), "+f"(d[55]), "+f"(d[56]), "+f"(d[57]), "+f"(d[58]), "+f"(d[59]), "+f"(d[60]), "+f"(d[61]), "+f"(d[62]), "+f"(d[63]), "+f"(d[64]), "+f"(d[65]), "+f"(d[66]), "+f"(d[67]), "+f"(d[68]), "+f"(d[69]), "+f"(d[70]), "+f"(d[71]), "+f"(d[72]), "+f"(d[73]), "+f"(d[74]), "+f"(d[75]), "+f"(d[76]), "+f"(d[77]), "+f"(d[78]), "+f"(d[79]), "+f"(d[80]), "+f"(d[81]), "+f"(d[82]), "+f"(d[83]), "+f"(d[84]), "+f"(d[85]), "+f"(d[86]), "+f"(d[87]), "+f"(d[88]), "+f"(d[89]), "+f"(d[90]), "+f"(d[91]), "+f"(d[92]), "+f"(d[93]), "+f"(d[94]), "+f"(d[95])
    : "r"(a0), "r"(a1), "r"(a2), "r"(a3), "l"(db), "r"(scale_d));
}

__device__ __forceinline__ void wgmma_n192_rs_tb(float (&d)[96], uint32_t a0, uint32_t a1, uint32_t a2, uint32_t a3, uint64_t db, int scale_d) {
  asm volatile("{\n.reg .pred p;\nsetp.ne.b32 p, %101, 0;\n"
    "wgmma.mma_async.sync.aligned.m64n192k16.f32.bf16.bf16 {%0, %1, %2, %3, %4, %5, %6, %7, %8, %9, %10, %11, %12, %13, %14, %15, %16, %17, %18, %19, %20, %21, %22, %23, %24, %25, %26, %27, %28, %29, %30, %31, %32, %33, %34, %35, %36, %37, %38, %39, %40, %41, %42, %43, %44, %45, %46, %47, %48, %49, %50, %51, %52, %53, %54, %55, %56, %57, %58, %59, %60, %61, %62, %63, %64, %65, %66, %67, %68, %69, %70, %71, %72, %73, %74, %75, %76, %77, %78, %79, %80, %81, %82, %83, %84, %85, %86, %87, %88, %89, %90, %91, %92, %93, %94, %95}, {%96, %97, %98, %99}, %100, p, 1, 1, 1;\n}\n"
    : "+f"(d[0]), "+f"(d[1]), "+f"(d[2]), "+f"(d[3]), "+f"(d[4]), "+f"(d[5]), "+f"(d[6]), "+f"(d[7]), "+f"(d[8]), "+f"(d[9]), "+f"(d[10]), "+f"(d[11]), "+f"(d[12]), "+f"(d[13]), "+f"(d[14]), "+f"(d[15]), "+f"(d[16]), "+f"(d[17]), "+f"(d[18]), "+f"(d[19]), "+f"(d[20]), "+f"(d[21]), "+f"(d[22]), "+f"(d[23]), "+f"(d[24]), "+f"(d[25]), "+f"(d[26]), "+f"(d[27]), "+f"(d[28]), "+f"(d[29]), "+f"(d[30]), "+f"(d[31]), "+f"(d[32]), "+f"(d[33]), "+f"(d[34]), "+f"(d[35]), "+f"(d[36]), "+f"(d[37]), "+f"(d[38]), "+f"(d[39]), "+f"(d[40]), "+f"(d[41]), "+f"(d[42]), "+f"(d[43]), "+f"(d[44]), "+f"(d[45]), "+f"(d[46]), "+f"(d[47]), "+f"(d[48]), "+f"(d[49]), "+f"(d[50]), "+f"(d[51]), "+f"(d[52]), "+f"(d[53]), "+f"(d[54]), "+f"(d[55]), "+f"(d[56]), "+f"(d[57]), "+f"(d[58]), "+f"(d[59]), "+f"(d[60]), "+f"(d[61]), "+f"(d[62]), "+f"(d[63]), "+f"(d[64]), "+f"(d[65]), "+f"(d[66]), "+f"(d[67]), "+f"(d[68]), "+f"(d[69]), "+f"(d[70]), "+f"(d[71]), "+f"(d[72]), "+f"(d[73]), "+f"(d[74]), "+f"(d[75]), "+f"(d[76]), "+f"(d[77]), "+f"(d[78]), "+f"(d[79]), "+f"(d[80]), "+f"(d[81]), "+f"(d[82]), "+f"(d[83]), "+f"(d[84]), "+f"(d[85]), "+f"(d[86]), "+f"(d[87]), "+f"(d[88]), "+f"(d[89]), "+f"(d[90]), "+f"(d[91]), "+f"(d[92]), "+f"(d[93]), "+f"(d[94]), "+f"(d[95])
    : "r"(a0), "r"(a1), "r"(a2), "r"(a3), "l"(db), "r"(scale_d));
}

__device__ __forceinline__ void wgmma_n56_rs(float (&d)[28], uint32_t a0, uint32_t a1, uint32_t a2, uint32_t a3, uint64_t db, int scale_d) {
  asm volatile("{\n.reg .pred p;\nsetp.ne.b32 p, %33, 0;\n"
    "wgmma.mma_async.sync.aligned.m64n56k16.f32.bf16.bf16 {%0, %1, %2, %3, %4, %5, %6, %7, %8, %9, %10, %11, %12, %13, %14, %15, %16, %17, %18, %19, %20, %21, %22, %23, %24, %25, %26, %27}, {%28, %29, %30, %31}, %32, p, 1, 1, 0;\n}\n"
    : "+f"(d[0]), "+f"(d[1]), "+f"(d[2]), "+f"(d[3]), "+f"(d[4]), "+f"(d[5]), "+f"(d[6]), "+f"(d[7]), "+f"(d[8]), "+f"(d[9]), "+f"(d[10]), "+f"(d[11]), "+f"(d[12]), "+f"(d[13]), "+f"(d[14]), "+f"(d[15]), "+f"(d[16]), "+f"(d[17]), "+f"(d[18]), "+f"(d[19]), "+f"(d[20]), "+f"(d[21]), "+f"(d[22]), "+f"(d[23]), "+f"(d[24]), "+f"(d[25]), "+f"(d[26]), "+f"(d[27])
    : "r"(a0), "r"(a1), "r"(a2), "r"(a3), "l"(db), "r"(scale_d));
}

__device__ __forceinline__ void acc_fence(float (&d)[96]) {
  asm volatile("" : "+f"(d[0]), "+f"(d[1]), "+f"(d[2]), "+f"(d[3]), "+f"(d[4]), "+f"(d[5]), "+f"(d[6]), "+f"(d[7]), "+f"(d[8]), "+f"(d[9]), "+f"(d[10]), "+f"(d[11]), "+f"(d[12]), "+f"(d[13]), "+f"(d[14]), "+f"(d[15]), "+f"(d[16]), "+f"(d[17]), "+f"(d[18]), "+f"(d[19]), "+f"(d[20]), "+f"(d[21]), "+f"(d[22]), "+f"(d[23]), "+f"(d[24]), "+f"(d[25]), "+f"(d[26]), "+f"(d[27]), "+f"(d[28]), "+f"(d[29]), "+f"(d[30]), "+f"(d[31]), "+f"(d[32]), "+f"(d[33]), "+f"(d[34]), "+f"(d[35]), "+f"(d[36]), "+f"(d[37]), "+f"(d[38]), "+f"(d[39]), "+f"(d[40]), "+f"(d[41]), "+f"(d[42]), "+f"(d[43]), "+f"(d[44]), "+f"(d[45]), "+f"(d[46]), "+f"(d[47]), "+f"(d[48]), "+f"(d[49]), "+f"(d[50]), "+f"(d[51]), "+f"(d[52]), "+f"(d[53]), "+f"(d[54]), "+f"(d[55]), "+f"(d[56]), "+f"(d[57]), "+f"(d[58]), "+f"(d[59]), "+f"(d[60]), "+f"(d[61]), "+f"(d[62]), "+f"(d[63]), "+f"(d[64]), "+f"(d[65]), "+f"(d[66]), "+f"(d[67]), "+f"(d[68]), "+f"(d[69]), "+f"(d[70]), "+f"(d[71]), "+f"(d[72]), "+f"(d[73]), "+f"(d[74]), "+f"(d[75]), "+f"(d[76]), "+f"(d[77]), "+f"(d[78]), "+f"(d[79]), "+f"(d[80]), "+f"(d[81]), "+f"(d[82]), "+f"(d[83]), "+f"(d[84]), "+f"(d[85]), "+f"(d[86]), "+f"(d[87]), "+f"(d[88]), "+f"(d[89]), "+f"(d[90]), "+f"(d[91]), "+f"(d[92]), "+f"(d[93]), "+f"(d[94]), "+f"(d[95]) :: "memory");
}

__device__ __forceinline__ void acc_fence(float (&d)[28]) {
  asm volatile("" : "+f"(d[0]), "+f"(d[1]), "+f"(d[2]), "+f"(d[3]), "+f"(d[4]), "+f"(d[5]), "+f"(d[6]), "+f"(d[7]), "+f"(d[8]), "+f"(d[9]), "+f"(d[10]), "+f"(d[11]), "+f"(d[12]), "+f"(d[13]), "+f"(d[14]), "+f"(d[15]), "+f"(d[16]), "+f"(d[17]), "+f"(d[18]), "+f"(d[19]), "+f"(d[20]), "+f"(d[21]), "+f"(d[22]), "+f"(d[23]), "+f"(d[24]), "+f"(d[25]), "+f"(d[26]), "+f"(d[27]) :: "memory");
}

constexpr int FW_LD = 200;
__global__ void __launch_bounds__(384) fold_weights_kernel(const __nv_bfloat16* __restrict__ wqkv_t, const __nv_bfloat16* __restrict__ wo_t,
                                    const __nv_bfloat16* __restrict__ wqkv_s, const __nv_bfloat16* __restrict__ wo_s) {
  extern __shared__ __align__(16) uint8_t fsm[];
  __nv_bfloat16* As = reinterpret_cast<__nv_bfloat16*>(fsm);
  float* part = reinterpret_cast<float*>(fsm + CH * FW_LD * 2);
  float* part2 = part + 16 * CH;
  float* cm = part2 + 16 * CH;
  float* Bs = cm + CH;
  const int mat = blockIdx.y, n0 = blockIdx.x * 16, tid = threadIdx.x;
  const __nv_bfloat16* wqkv = (mat < 2) ? wqkv_t : wqkv_s;
  const __nv_bfloat16* wo = (mat < 2) ? wo_t : wo_s;
  const bool isM = (mat & 1) == 0;
  const int offA = isM ? 0 : 2 * CH;
  const int cg = tid % 24, rg = tid / 24;
  {
    uint4 va[12], vb[12];
#pragma unroll
    for (int i = 0; i < 12; i++) va[i] = *reinterpret_cast<const uint4*>(wqkv + (rg * 12 + i) * 3 * CH + offA + cg * 8);
    if (isM) {
#pragma unroll
      for (int i = 0; i < 12; i++) vb[i] = *reinterpret_cast<const uint4*>(wqkv + (rg * 12 + i) * 3 * CH + CH + cg * 8);
    } else {
#pragma unroll
      for (int i = 0; i < 12; i++) vb[i] = make_uint4(0, 0, 0, 0);
    }
    float sa[8] = {0.f, 0.f, 0.f, 0.f, 0.f, 0.f, 0.f, 0.f}, sb[8] = {0.f, 0.f, 0.f, 0.f, 0.f, 0.f, 0.f, 0.f};
#pragma unroll
    for (int i = 0; i < 12; i++) {
      *reinterpret_cast<uint4*>(As + (rg * 12 + i) * FW_LD + cg * 8) = va[i];
      sa[0] += bf_lo(va[i].x); sa[1] += bf_hi(va[i].x); sa[2] += bf_lo(va[i].y); sa[3] += bf_hi(va[i].y);
      sa[4] += bf_lo(va[i].z); sa[5] += bf_hi(va[i].z); sa[6] += bf_lo(va[i].w); sa[7] += bf_hi(va[i].w);
      sb[0] += bf_lo(vb[i].x); sb[1] += bf_hi(vb[i].x); sb[2] += bf_lo(vb[i].y); sb[3] += bf_hi(vb[i].y);
      sb[4] += bf_lo(vb[i].z); sb[5] += bf_hi(vb[i].z); sb[6] += bf_lo(vb[i].w); sb[7] += bf_hi(vb[i].w);
    }
#pragma unroll
    for (int e = 0; e < 8; e++) { part[rg * CH + cg * 8 + e] = sa[e]; part2[rg * CH + cg * 8 + e] = sb[e]; }
  }
  __syncthreads();
  if (tid < CH) {
    float s = 0.f, s2 = 0.f;
#pragma unroll
    for (int r = 0; r < 16; r++) { s += part[r * CH + tid]; s2 += part2[r * CH + tid]; }
    cm[tid] = s * (1.0f / CH);
    const float cmB = s2 * (1.0f / CH);
#pragma unroll
    for (int n = 0; n < 16; n++)
      Bs[n * 196 + tid] = isM ? (__bfloat162float(wqkv[(n0 + n) * 3 * CH + CH + tid]) - cmB) : __bfloat162float(wo[tid * CH + n0 + n]);
  }
  __syncthreads();
  const int k = tid >> 1, nh = (tid & 1) * 8;
  float acc[8];
#pragma unroll
  for (int n = 0; n < 8; n++) acc[n] = 0.f;
#pragma unroll 4
  for (int c = 0; c < CH; c += 4) {
    const uint2 u = *reinterpret_cast<const uint2*>(As + k * FW_LD + c);
    const float4 m4 = *reinterpret_cast<const float4*>(cm + c);
    const float a0 = bf_lo(u.x) - m4.x, a1 = bf_hi(u.x) - m4.y, a2 = bf_lo(u.y) - m4.z, a3 = bf_hi(u.y) - m4.w;
#pragma unroll
    for (int n = 0; n < 8; n++) {
      const float4 b = *reinterpret_cast<const float4*>(Bs + (nh + n) * 196 + c);
      acc[n] = fmaf(a0, b.x, acc[n]); acc[n] = fmaf(a1, b.y, acc[n]);
      acc[n] = fmaf(a2, b.z, acc[n]); acc[n] = fmaf(a3, b.w, acc[n]);
    }
  }
  const int p = k >> 6, kc = k & 63;
#pragma unroll
  for (int n = 0; n < 8; n++) {
    const int nn = n0 + nh + n;
    g_w[mat][p * (CH * 64) + nn * 64 + (((kc >> 3) ^ (nn & 7)) << 3) + (kc & 7)] = __float2bfloat16(acc[n]);
  }
}
constexpr int FW_SMEM = CH * FW_LD * 2 + (32 * CH + CH + 16 * 196) * 4;

struct Params {
  int role;
};

__device__ __forceinline__ uint32_t frag_addr(uint32_t slot_rowoff, uint32_t sw, int hiblk, int kk) {
  const int ci = 2 * kk + hiblk;
  return slot_rowoff + (ci >> 3) * PANEL_X + ((((uint32_t)ci & 7u) ^ sw) << 4);
}

__device__ __forceinline__ float row_rstd(uint32_t slot, int w, int lane) {
  const int row = 16 * w + (lane >> 1), half = lane & 1;
  const uint32_t rbase = slot + row * 128, sw = row & 7;
  float s0 = 0.f, s1 = 0.f, s2 = 0.f, s3 = 0.f, q0 = 0.f, q1 = 0.f, q2 = 0.f, q3 = 0.f;
#pragma unroll
  for (int i = 0; i < 12; i++) {
    const int c = half * 12 + i;
    const uint4 v = lds128(rbase + (c >> 3) * PANEL_X + ((((uint32_t)c & 7u) ^ sw) << 4));
    float lo, hi;
    lo = bf_lo(v.x); hi = bf_hi(v.x); s0 += lo; s1 += hi; q0 = fmaf(lo, lo, q0); q1 = fmaf(hi, hi, q1);
    lo = bf_lo(v.y); hi = bf_hi(v.y); s2 += lo; s3 += hi; q2 = fmaf(lo, lo, q2); q3 = fmaf(hi, hi, q3);
    lo = bf_lo(v.z); hi = bf_hi(v.z); s0 += lo; s1 += hi; q0 = fmaf(lo, lo, q0); q1 = fmaf(hi, hi, q1);
    lo = bf_lo(v.w); hi = bf_hi(v.w); s2 += lo; s3 += hi; q2 = fmaf(lo, lo, q2); q3 = fmaf(hi, hi, q3);
  }
  float s = (s0 + s1) + (s2 + s3), ss = (q0 + q1) + (q2 + q3);
  s += __shfl_xor_sync(0xffffffffu, s, 1);
  ss += __shfl_xor_sync(0xffffffffu, ss, 1);
  const float mean = s * (1.0f / CH);
  const float var = fmaxf(ss * (1.0f / CH) - mean * mean, 0.f);
  return rsqrtf(var + 1e-5f);
}

__global__ void __launch_bounds__(NWG * 128 + 128, 1)
swin_main_kernel(const __grid_constant__ CUtensorMap map_in, const __grid_constant__ CUtensorMap map_out, const int role) {
  extern __shared__ __align__(1024) uint8_t smem_raw[];
  const uint32_t sbase = smem_u32(smem_raw);
  const int tid = threadIdx.x, wg = tid >> 7, t128 = tid & 127, w = t128 >> 5, lane = tid & 31;
  const int g = lane >> 2, q = lane & 3;

  const uint32_t bar_w = sbase + SMEM_MISC;
  float* rbuf = reinterpret_cast<float*>(smem_raw + SMEM_RBUF) + wg * 64;

  if (tid == 0) {
    mbar_init(bar_w, 1);
    for (int i = 0; i < NSLOT; i++) { mbar_init(sbase + SMEM_MISC + 8 + 8 * i, 1); mbar_init(sbase + SMEM_MISC + 64 + 8 * i, 128); }
    asm volatile("fence.mbarrier_init.release.cluster;" ::: "memory");
  }
  for (int i = tid; i < NSLOT * SLOT_BYTES / 16; i += NWG * 128 + 128)
    *reinterpret_cast<uint4*>(smem_raw + SMEM_SLOT + i * 16) = make_uint4(0, 0, 0, 0);
  fence_proxy_async();
  __syncthreads();

  const int nunits = role == 0 ? NTILE_A : NUNIT_B;
  const int ustride = gridDim.x;
  const int nj = (nunits - (int)blockIdx.x + ustride - 1) / ustride;
  const uint32_t tx_bytes = role == 0 ? SLOT_BYTES : 3 * 49 * 128;

  auto coords = [&](int j, int& c1, int& c2, int& c3) {
    const int u = blockIdx.x + j * ustride;
    if (role == 0) { c1 = 0; c2 = (u % 14) * 16; c3 = u / 14; }
    else { const int t = u & 3, wx = (u >> 2) & 31, wy = u >> 7; c1 = wx * 7; c2 = wy * 7; c3 = t; }
  };
  auto issue_load = [&](int j) {
    int c1, c2, c3; coords(j, c1, c2, c3);
    const int sl = j % NSLOT;
    const uint32_t bar = sbase + SMEM_MISC + 8 + 8 * sl;
    mbar_expect_tx(bar, tx_bytes);
#pragma unroll
    for (int p = 0; p < 3; p++) tma_load_4d(sbase + SMEM_SLOT + sl * SLOT_BYTES + p * PANEL_X, &map_in, p * 64, c1, c2, c3, bar);
  };
  auto prefetch_l2 = [&](int j) {
    if (j < nj) {
      int c1, c2, c3; coords(j, c1, c2, c3);
#pragma unroll
      for (int p = 0; p < 3; p++) tma_prefetch_4d(&map_in, p * 64, c1, c2, c3);
    }
  };

  if (tid >= NWG * 128) {
    asm volatile("setmaxnreg.dec.sync.aligned.u32 40;");
    if (tid == NWG * 128) {
      mbar_expect_tx(bar_w, 2 * WMAT_BYTES);
      bulk_load(sbase + SMEM_W0, &g_w[role * 2][0], WMAT_BYTES, bar_w);
      bulk_load(sbase + SMEM_W1, &g_w[role * 2 + 1][0], WMAT_BYTES, bar_w);
      for (int j = 0; j < NSLOT && j < nj; j++) issue_load(j);
      prefetch_l2(NSLOT); prefetch_l2(NSLOT + 1);
      for (int j = 0; j < nj; j++) {
        const int sl = j % NSLOT;
        mbar_wait(sbase + SMEM_MISC + 64 + 8 * sl, (j / NSLOT) & 1);
        int c1, c2, c3; coords(j, c1, c2, c3);
#pragma unroll
        for (int p = 0; p < 3; p++) tma_store_4d(&map_out, sbase + SMEM_SLOT + sl * SLOT_BYTES + p * PANEL_X, p * 64, c1, c2, c3);
        bulk_commit();
        bulk_wait_read0();
        if (j + NSLOT < nj) issue_load(j + NSLOT);
        prefetch_l2(j + NSLOT + 2);
      }
      bulk_wait0();
    }
    return;
  }
  asm volatile("setmaxnreg.inc.sync.aligned.u32 232;");
  mbar_wait(bar_w, 0);

  const int blk = lane >> 3;
  const int frow = 16 * w + (lane & 7) + ((blk & 1) << 3);
  const uint32_t fsw = frow & 7;
  const int fhi = blk >> 1;

  const uint64_t dW0 = make_desc(sbase + SMEM_W0, 16, 1024);
  const uint64_t dW1 = make_desc(sbase + SMEM_W1, 16, 1024);

  const float scale_l2e = 0.07216878364870322f * 1.4426950408889634f;

  for (int j = wg; j < nj; j += NWG) {
    const int sl = j % NSLOT;
    const uint32_t slot = sbase + SMEM_SLOT + sl * SLOT_BYTES;
    const uint32_t frowoff = slot + frow * 128;
    const uint64_t dX = make_desc(slot, 16, 1024);
    const uint64_t dXmn = make_desc(slot, PANEL_X, 1024);
    PH(0);
    mbar_wait(sbase + SMEM_MISC + 8 + 8 * sl, (j / NSLOT) & 1);
    PH(1);

    float acc[96];
    wgmma_fence();
#pragma unroll
    for (int kk = 0; kk < 12; kk++) {
      const uint32_t off = (kk >> 2) * PANEL_X + (kk & 3) * 32;
      const uint32_t offw = (kk >> 2) * PANEL_W + (kk & 3) * 32;
      wgmma_n192_ss(acc, dX + (off >> 4), dW0 + (offw >> 4), kk);
    }
    wgmma_commit();
    PH(2);
    const float rmine = row_rstd(slot, w, lane);
    PH(3);
    uint32_t fr[48];

    if (role == 0) {
      wgmma_wait0(); acc_fence(acc);
      PH(4);
#pragma unroll
      for (int i = 0; i < 48; i++) fr[i] = pack_bf16(acc[2 * i], acc[2 * i + 1]);
      float d0[4] = {0.f, 0.f, 0.f, 0.f}, d1[4] = {0.f, 0.f, 0.f, 0.f};
#pragma unroll
      for (int kk = 0; kk < 12; kk++) {
        uint32_t b0, b1, b2, b3;
        ldsm_x4(frag_addr(frowoff, fsw, fhi, kk), b0, b1, b2, b3);
        mma_16816(d0[0], d0[1], d0[2], d0[3], fr[4 * kk], fr[4 * kk + 1], fr[4 * kk + 2], fr[4 * kk + 3], b0, b2);
        mma_16816(d1[0], d1[1], d1[2], d1[3], fr[4 * kk], fr[4 * kk + 1], fr[4 * kk + 2], fr[4 * kk + 3], b1, b3);
      }
      const float rA = __shfl_sync(0xffffffffu, rmine, 2 * g);
      const float rB = __shfl_sync(0xffffffffu, rmine, 2 * g + 16);
      const float k0 = __shfl_sync(0xffffffffu, rmine, 4 * q);
      const float k1 = __shfl_sync(0xffffffffu, rmine, 4 * q + 2);
      const float k2 = __shfl_sync(0xffffffffu, rmine, 4 * q + 16);
      const float k3 = __shfl_sync(0xffffffffu, rmine, 4 * q + 18);
      const bool valid = (g >> 2) == (q >> 1);
      float sa0 = d0[0] * k0 * (rA * scale_l2e), sa1 = d0[1] * k1 * (rA * scale_l2e);
      float sb0 = d1[2] * k2 * (rB * scale_l2e), sb1 = d1[3] * k3 * (rB * scale_l2e);
      float ma = fmaxf(sa0, sa1), mb = fmaxf(sb0, sb1);
      ma = fmaxf(ma, __shfl_xor_sync(0xffffffffu, ma, 1));
      mb = fmaxf(mb, __shfl_xor_sync(0xffffffffu, mb, 1));
      const float ea0 = exp2f(sa0 - ma), ea1 = exp2f(sa1 - ma);
      const float eb0 = exp2f(sb0 - mb), eb1 = exp2f(sb1 - mb);
      float suma = ea0 + ea1, sumb = eb0 + eb1;
      suma += __shfl_xor_sync(0xffffffffu, suma, 1);
      sumb += __shfl_xor_sync(0xffffffffu, sumb, 1);
      const float ia = __fdividef(1.f, suma), ib = __fdividef(1.f, sumb);
      const uint32_t pa0 = valid ? pack_bf16(ea0 * ia * k0, ea1 * ia * k1) : 0u;
      const uint32_t pa3 = valid ? pack_bf16(eb0 * ib * k2, eb1 * ib * k3) : 0u;
      PH(5);
#pragma unroll
      for (int jj = 0; jj < 12; jj++) {
        uint32_t b0, b1, b2, b3;
        ldsm_x4_t(frag_addr(frowoff, fsw, fhi, jj), b0, b1, b2, b3);
        acc[8 * jj + 0] = 0.f; acc[8 * jj + 1] = 0.f; acc[8 * jj + 2] = 0.f; acc[8 * jj + 3] = 0.f;
        acc[8 * jj + 4] = 0.f; acc[8 * jj + 5] = 0.f; acc[8 * jj + 6] = 0.f; acc[8 * jj + 7] = 0.f;
        mma_16816(acc[8 * jj + 0], acc[8 * jj + 1], acc[8 * jj + 2], acc[8 * jj + 3], pa0, 0u, 0u, pa3, b0, b1);
        mma_16816(acc[8 * jj + 4], acc[8 * jj + 5], acc[8 * jj + 6], acc[8 * jj + 7], pa0, 0u, 0u, pa3, b2, b3);
      }
    } else {
      if ((lane & 1) == 0) rbuf[16 * w + (lane >> 1)] = rmine;
      wg_bar(1 + wg);
      wgmma_wait0(); acc_fence(acc);
      PH(4);
#pragma unroll
      for (int i = 0; i < 48; i++) fr[i] = pack_bf16(acc[2 * i], acc[2 * i + 1]);
      float s[28];
      wgmma_fence();
#pragma unroll
      for (int kk = 0; kk < 12; kk++) {
        const uint32_t off = (kk >> 2) * PANEL_X + (kk & 3) * 32;
        wgmma_n56_rs(s, fr[4 * kk], fr[4 * kk + 1], fr[4 * kk + 2], fr[4 * kk + 3], dX + (off >> 4), kk);
      }
      wgmma_commit();
      float rj[14];
#pragma unroll
      for (int j = 0; j < 7; j++) {
        const float2 v = *reinterpret_cast<const float2*>(&rbuf[8 * j + 2 * q]);
        rj[2 * j] = v.x; rj[2 * j + 1] = v.y;
      }
      const float ri0 = rbuf[16 * w + g] * scale_l2e, ri1 = rbuf[16 * w + g + 8] * scale_l2e;
      wgmma_wait0(); acc_fence(s);
      PH(5);
      float m0 = -INFINITY, m1 = -INFINITY;
#pragma unroll
      for (int j = 0; j < 7; j++) {
#pragma unroll
        for (int e = 0; e < 2; e++) {
          const bool ok = (j < 6) || (2 * q + e == 0);
          float v0 = s[4 * j + e] * rj[2 * j + e] * ri0;
          float v1 = s[4 * j + 2 + e] * rj[2 * j + e] * ri1;
          v0 = ok ? v0 : -INFINITY; v1 = ok ? v1 : -INFINITY;
          s[4 * j + e] = v0; s[4 * j + 2 + e] = v1;
          m0 = fmaxf(m0, v0); m1 = fmaxf(m1, v1);
        }
      }
      m0 = fmaxf(m0, __shfl_xor_sync(0xffffffffu, m0, 1)); m0 = fmaxf(m0, __shfl_xor_sync(0xffffffffu, m0, 2));
      m1 = fmaxf(m1, __shfl_xor_sync(0xffffffffu, m1, 1)); m1 = fmaxf(m1, __shfl_xor_sync(0xffffffffu, m1, 2));
      float sum0 = 0.f, sum1 = 0.f;
#pragma unroll
      for (int j = 0; j < 7; j++) {
#pragma unroll
        for (int e = 0; e < 2; e++) {
          const float e0 = exp2f(s[4 * j + e] - m0), e1 = exp2f(s[4 * j + 2 + e] - m1);
          s[4 * j + e] = e0; s[4 * j + 2 + e] = e1;
          sum0 += e0; sum1 += e1;
        }
      }
      sum0 += __shfl_xor_sync(0xffffffffu, sum0, 1); sum0 += __shfl_xor_sync(0xffffffffu, sum0, 2);
      sum1 += __shfl_xor_sync(0xffffffffu, sum1, 1); sum1 += __shfl_xor_sync(0xffffffffu, sum1, 2);
      const float i0 = __fdividef(1.f, sum0), i1 = __fdividef(1.f, sum1);
      uint32_t pa[16];
#pragma unroll
      for (int j = 0; j < 7; j++) {
        pa[(j >> 1) * 4 + (j & 1) * 2 + 0] = pack_bf16(s[4 * j] * i0 * rj[2 * j], s[4 * j + 1] * i0 * rj[2 * j + 1]);
        pa[(j >> 1) * 4 + (j & 1) * 2 + 1] = pack_bf16(s[4 * j + 2] * i1 * rj[2 * j], s[4 * j + 3] * i1 * rj[2 * j + 1]);
      }
      pa[14] = 0u; pa[15] = 0u;
      PH(6);
      wgmma_fence();
#pragma unroll
      for (int kk = 0; kk < 4; kk++)
        wgmma_n192_rs_tb(acc, pa[4 * kk], pa[4 * kk + 1], pa[4 * kk + 2], pa[4 * kk + 3], dXmn + ((kk * 2048) >> 4), kk);
      wgmma_commit();
      wgmma_wait0(); acc_fence(acc);
    }

    PH(7);
#pragma unroll
    for (int i = 0; i < 48; i++) fr[i] = pack_bf16(acc[2 * i], acc[2 * i + 1]);
    wgmma_fence();
#pragma unroll
    for (int kk = 0; kk < 12; kk++) {
      const uint32_t offw = (kk >> 2) * PANEL_W + (kk & 3) * 32;
      wgmma_n192_rs(acc, fr[4 * kk], fr[4 * kk + 1], fr[4 * kk + 2], fr[4 * kk + 3], dW1 + (offw >> 4), kk);
    }
    wgmma_commit();
    wgmma_wait0(); acc_fence(acc);
    PH(8);
    wg_bar(1 + wg);
    PH(9);
#pragma unroll
    for (int kk = 0; kk < 12; kk++) {
      const uint32_t a = frag_addr(frowoff, fsw, fhi, kk);
      uint32_t x0, x1, x2, x3;
      ldsm_x4(a, x0, x1, x2, x3);
      const uint32_t o0 = add_bf16x2(x0, pack_bf16(acc[8 * kk + 0], acc[8 * kk + 1]));
      const uint32_t o1 = add_bf16x2(x1, pack_bf16(acc[8 * kk + 2], acc[8 * kk + 3]));
      const uint32_t o2 = add_bf16x2(x2, pack_bf16(acc[8 * kk + 4], acc[8 * kk + 5]));
      const uint32_t o3 = add_bf16x2(x3, pack_bf16(acc[8 * kk + 6], acc[8 * kk + 7]));
      stsm_x4(a, o0, o1, o2, o3);
    }
    PH(10);
    fence_proxy_async();
    mbar_arrive(sbase + SMEM_MISC + 64 + 8 * sl);
    PH(11);
  }
}

typedef CUresult (*EncodeTiledFn)(CUtensorMap*, CUtensorMapDataType, cuuint32_t, void*, const cuuint64_t*, const cuuint64_t*,
                                  const cuuint32_t*, const cuuint32_t*, CUtensorMapInterleave, CUtensorMapSwizzle,
                                  CUtensorMapL2promotion, CUtensorMapFloatOOBfill);

bool make_map(EncodeTiledFn fn, CUtensorMap* m, void* base, bool pixel_major) {
  cuuint64_t dims[4]; cuuint64_t strides[3]; cuuint32_t box[4]; cuuint32_t es[4] = {1, 1, 1, 1};
  const cuuint64_t sC = (cuuint64_t)CH * 2, sW = sC * WW, sT = sW * HH;
  if (pixel_major) {
    dims[0] = CH; dims[1] = TT; dims[2] = WW; dims[3] = HH;
    strides[0] = sT; strides[1] = sC; strides[2] = sW;
    box[0] = 64; box[1] = 4; box[2] = 16; box[3] = 1;
  } else {
    dims[0] = CH; dims[1] = WW; dims[2] = HH; dims[3] = TT;
    strides[0] = sC; strides[1] = sW; strides[2] = sT;
    box[0] = 64; box[1] = 7; box[2] = 7; box[3] = 1;
  }
  return fn(m, CU_TENSOR_MAP_DATA_TYPE_BFLOAT16, 4, base, dims, strides, box, es, CU_TENSOR_MAP_INTERLEAVE_NONE,
            CU_TENSOR_MAP_SWIZZLE_128B, CU_TENSOR_MAP_L2_PROMOTION_L2_256B, CU_TENSOR_MAP_FLOAT_OOB_FILL_NONE) == CUDA_SUCCESS;
}

}

extern "C" void kernel_launch(void* const* d_in, const int* in_sizes, int n_in, void* d_out, int out_size) {
  const __nv_bfloat16* x = (const __nv_bfloat16*)d_in[0];
  const __nv_bfloat16* wqkv_t = (const __nv_bfloat16*)d_in[1];
  const __nv_bfloat16* wo_t = (const __nv_bfloat16*)d_in[2];
  const __nv_bfloat16* wqkv_s = (const __nv_bfloat16*)d_in[3];
  const __nv_bfloat16* wo_s = (const __nv_bfloat16*)d_in[4];

  static bool init = false;
  static CUtensorMap mA_in, mA_out, mB_in, mB_out;
  static void* last_x = nullptr; static void* last_out = nullptr;
  static int nsm = 132;
  if (!init || last_x != d_in[0] || last_out != d_out) {
    void* fnp = nullptr; cudaDriverEntryPointQueryResult qr;
    cudaGetDriverEntryPoint("cuTensorMapEncodeTiled", &fnp, cudaEnableDefault, &qr);
    EncodeTiledFn fn = (EncodeTiledFn)fnp;
    void* x1p = nullptr; cudaGetSymbolAddress(&x1p, g_x1);
    make_map(fn, &mA_in, (void*)x, true);
    make_map(fn, &mA_out, x1p, true);
    make_map(fn, &mB_in, x1p, false);
    make_map(fn, &mB_out, d_out, false);
    cudaFuncSetAttribute(fold_weights_kernel, cudaFuncAttributeMaxDynamicSharedMemorySize, FW_SMEM);
    cudaFuncSetAttribute(swin_main_kernel, cudaFuncAttributeMaxDynamicSharedMemorySize, SMEM_TOTAL);
    cudaDeviceGetAttribute(&nsm, cudaDevAttrMultiProcessorCount, 0);
    init = true; last_x = d_in[0]; last_out = d_out;
  }
  fold_weights_kernel<<<dim3(12, 4), 384, FW_SMEM>>>(wqkv_t, wo_t, wqkv_s, wo_s);
  swin_main_kernel<<<nsm, NWG * 128 + 128, SMEM_TOTAL>>>(mA_in, mA_out, 0);
  swin_main_kernel<<<nsm, NWG * 128 + 128, SMEM_TOTAL>>>(mB_in, mB_out, 1);
}
```

```cpp
#include <cuda_runtime.h>
#include <cuda_bf16.h>
#include <cuda.h>
#include <stdint.h>

namespace {

constexpr int CH = 192;
constexpr int TT = 4, HH = 224, WW = 224;
constexpr int NTOK = TT * HH * WW;
constexpr int PANEL_X = 64 * 128;
constexpr int SLOT_BYTES = 3 * PANEL_X;
constexpr int PANEL_W = 192 * 128;
constexpr int WMAT_BYTES = 3 * PANEL_W;
constexpr int NWG = 3;
constexpr int NSLOT = 3;
constexpr int SMEM_W0 = 0;
constexpr int SMEM_W1 = WMAT_BYTES;
constexpr int SMEM_SLOT = 2 * WMAT_BYTES;
constexpr int SMEM_MISC = SMEM_SLOT + NSLOT * SLOT_BYTES;
constexpr int SMEM_RBUF = SMEM_MISC + 128;
constexpr int SMEM_TOTAL = SMEM_RBUF + NWG * 64 * 4;

constexpr int NTILE_A = HH * (WW / 16);
constexpr int NUNIT_B = 32 * 32 * 4;

__device__ __nv_bfloat16 g_x1[(size_t)NTOK * CH];
__device__ __align__(1024) __nv_bfloat16 g_w[4][CH * CH];

#define PH(i) do {} while (0)
__device__ __forceinline__ uint32_t smem_u32(const void* p) { return (uint32_t)__cvta_generic_to_shared(p); }

__device__ __forceinline__ void mbar_init(uint32_t bar, uint32_t count) {
  asm volatile("mbarrier.init.shared::cta.b64 [%0], %1;" :: "r"(bar), "r"(count));
}
__device__ __forceinline__ void mbar_expect_tx(uint32_t bar, uint32_t bytes) {
  asm volatile("mbarrier.arrive.expect_tx.shared::cta.b64 _, [%0], %1;" :: "r"(bar), "r"(bytes) : "memory");
}
__device__ __forceinline__ void mbar_arrive(uint32_t bar) {
  asm volatile("mbarrier.arrive.shared::cta.b64 _, [%0];" :: "r"(bar) : "memory");
}
__device__ __forceinline__ void mbar_wait(uint32_t bar, uint32_t parity) {
  asm volatile(
    "{\n.reg .pred p;\n"
    "WAIT_%=:\n"
    "mbarrier.try_wait.parity.shared::cta.b64 p, [%0], %1;\n"
    "@p bra DONE_%=;\n"
    "bra WAIT_%=;\n"
    "DONE_%=:\n}\n" :: "r"(bar), "r"(parity) : "memory");
}
__device__ __forceinline__ void tma_load_4d(uint32_t dst, const CUtensorMap* map, int c0, int c1, int c2, int c3, uint32_t bar) {
  asm volatile("cp.async.bulk.tensor.4d.shared::cluster.global.tile.mbarrier::complete_tx::bytes [%0], [%1, {%2, %3, %4, %5}], [%6];"
    :: "r"(dst), "l"(map), "r"(c0), "r"(c1), "r"(c2), "r"(c3), "r"(bar) : "memory");
}
__device__ __forceinline__ void tma_prefetch_4d(const CUtensorMap* map, int c0, int c1, int c2, int c3) {
  asm volatile("cp.async.bulk.prefetch.tensor.4d.L2.global.tile [%0, {%1, %2, %3, %4}];"
    :: "l"(map), "r"(c0), "r"(c1), "r"(c2), "r"(c3) : "memory");
}
__device__ __forceinline__ void tma_store_4d(const CUtensorMap* map, uint32_t src, int c0, int c1, int c2, int c3) {
  asm volatile("cp.async.bulk.tensor.4d.global.shared::cta.tile.bulk_group [%0, {%1, %2, %3, %4}], [%5];"
    :: "l"(map), "r"(c0), "r"(c1), "r"(c2), "r"(c3), "r"(src) : "memory");
}
__device__ __forceinline__ void bulk_load(uint32_t dst, const void* src, uint32_t bytes, uint32_t bar) {
  asm volatile("cp.async.bulk.shared::cluster.global.mbarrier::complete_tx::bytes [%0], [%1], %2, [%3];"
    :: "r"(dst), "l"(src), "r"(bytes), "r"(bar) : "memory");
}
__device__ __forceinline__ void bulk_commit() { asm volatile("cp.async.bulk.commit_group;" ::: "memory"); }
__device__ __forceinline__ void bulk_wait_read0() { asm volatile("cp.async.bulk.wait_group.read 0;" ::: "memory"); }
__device__ __forceinline__ void bulk_wait0() { asm volatile("cp.async.bulk.wait_group 0;" ::: "memory"); }
__device__ __forceinline__ void fence_proxy_async() { asm volatile("fence.proxy.async.shared::cta;" ::: "memory"); }
__device__ __forceinline__ void wg_bar(int id) { asm volatile("bar.sync %0, 128;" :: "r"(id) : "memory"); }
__device__ __forceinline__ void wgmma_fence() { asm volatile("wgmma.fence.sync.aligned;" ::: "memory"); }
__device__ __forceinline__ void wgmma_commit() { asm volatile("wgmma.commit_group.sync.aligned;" ::: "memory"); }
__device__ __forceinline__ void wgmma_wait0() { asm volatile("wgmma.wait_group.sync.aligned 0;" ::: "memory"); }

__device__ __forceinline__ uint64_t make_desc(uint32_t saddr, uint32_t lbo, uint32_t sbo) {
  return (uint64_t)((saddr & 0x3FFFF) >> 4) | ((uint64_t)((lbo & 0x3FFFF) >> 4) << 16) |
         ((uint64_t)((sbo & 0x3FFFF) >> 4) << 32) | ((uint64_t)1 << 62);
}
__device__ __forceinline__ uint32_t pack_bf16(float lo, float hi) {
  uint32_t r; asm("cvt.rn.bf16x2.f32 %0, %1, %2;" : "=r"(r) : "f"(hi), "f"(lo)); return r;
}
__device__ __forceinline__ uint32_t add_bf16x2(uint32_t a, uint32_t b) {
  uint32_t r; asm("add.rn.bf16x2 %0, %1, %2;" : "=r"(r) : "r"(a), "r"(b)); return r;
}
__device__ __forceinline__ float bf_lo(uint32_t u) { return __uint_as_float(u << 16); }
__device__ __forceinline__ float bf_hi(uint32_t u) { return __uint_as_float(u & 0xffff0000u); }
__device__ __forceinline__ void ldsm_x4(uint32_t addr, uint32_t& r0, uint32_t& r1, uint32_t& r2, uint32_t& r3) {
  asm volatile("ldmatrix.sync.aligned.m8n8.x4.shared.b16 {%0,%1,%2,%3}, [%4];"
    : "=r"(r0), "=r"(r1), "=r"(r2), "=r"(r3) : "r"(addr) : "memory");
}
__device__ __forceinline__ void ldsm_x4_t(uint32_t addr, uint32_t& r0, uint32_t& r1, uint32_t& r2, uint32_t& r3) {
  asm volatile("ldmatrix.sync.aligned.m8n8.x4.trans.shared.b16 {%0,%1,%2,%3}, [%4];"
    : "=r"(r0), "=r"(r1), "=r"(r2), "=r"(r3) : "r"(addr) : "memory");
}
__device__ __forceinline__ void stsm_x4(uint32_t addr, uint32_t r0, uint32_t r1, uint32_t r2, uint32_t r3) {
  asm volatile("stmatrix.sync.aligned.m8n8.x4.shared.b16 [%0], {%1,%2,%3,%4};"
    :: "r"(addr), "r"(r0), "r"(r1), "r"(r2), "r"(r3) : "memory");
}
__device__ __forceinline__ void mma_16816(float& d0, float& d1, float& d2, float& d3,
                                          uint32_t a0, uint32_t a1, uint32_t a2, uint32_t a3, uint32_t b0, uint32_t b1) {
  asm volatile("mma.sync.aligned.m16n8k16.row.col.f32.bf16.bf16.f32 {%0,%1,%2,%3}, {%4,%5,%6,%7}, {%8,%9}, {%0,%1,%2,%3};"
    : "+f"(d0), "+f"(d1), "+f"(d2), "+f"(d3) : "r"(a0), "r"(a1), "r"(a2), "r"(a3), "r"(b0), "r"(b1));
}
__device__ __forceinline__ uint4 lds128(uint32_t addr) {
  uint4 v; asm volatile("ld.shared.v4.u32 {%0,%1,%2,%3}, [%4];" : "=r"(v.x), "=r"(v.y), "=r"(v.z), "=r"(v.w) : "r"(addr) : "memory");
  return v;
}

__device__ __forceinline__ void wgmma_n192_ss(float (&d)[96], uint64_t da, uint64_t db, int scale_d) {
  asm volatile("{\n.reg .pred p;\nsetp.ne.b32 p, %98, 0;\n"
    "wgmma.mma_async.sync.aligned.m64n192k16.f32.bf16.bf16 {%0, %1, %2, %3, %4, %5, %6, %7, %8, %9, %10, %11, %12, %13, %14, %15, %16, %17, %18, %19, %20, %21, %22, %23, %24, %25, %26, %27, %28, %29, %30, %31, %32, %33, %34, %35, %36, %37, %38, %39, %40, %41, %42, %43, %44, %45, %46, %47, %48, %49, %50, %51, %52, %53, %54, %55, %56, %57, %58, %59, %60, %61, %62, %63, %64, %65, %66, %67, %68, %69, %70, %71, %72, %73, %74, %75, %76, %77, %78, %79, %80, %81, %82, %83, %84, %85, %86, %87, %88, %89, %90, %91, %92, %93, %94, %95}, %96, %97, p, 1, 1, 0, 0;\n}\n"
    : "+f"(d[0]), "+f"(d[1]), "+f"(d[2]), "+f"(d[3]), "+f"(d[4]), "+f"(d[5]), "+f"(d[6]), "+f"(d[7]), "+f"(d[8]), "+f"(d[9]), "+f"(d[10]), "+f"(d[11]), "+f"(d[12]), "+f"(d[13]), "+f"(d[14]), "+f"(d[15]), "+f"(d[16]), "+f"(d[17]), "+f"(d[18]), "+f"(d[19]), "+f"(d[20]), "+f"(d[21]), "+f"(d[22]), "+f"(d[23]), "+f"(d[24]), "+f"(d[25]), "+f"(d[26]), "+f"(d[27]), "+f"(d[28]), "+f"(d[29]), "+f"(d[30]), "+f"(d[31]), "+f"(d[32]), "+f"(d[33]), "+f"(d[34]), "+f"(d[35]), "+f"(d[36]), "+f"(d[37]), "+f"(d[38]), "+f"(d[39]), "+f"(d[40]), "+f"(d[41]), "+f"(d[42]), "+f"(d[43]), "+f"(d[44]), "+f"(d[45]), "+f"(d[46]), "+f"(d[47]), "+f"(d[48]), "+f"(d[49]), "+f"(d[50]), "+f"(d[51]), "+f"(d[52]), "+f"(d[53]), "+f"(d[54]), "+f"(d[55]), "+f"(d[56]), "+f"(d[57]), "+f"(d[58]), "+f"(d[59]), "+f"(d[60]), "+f"(d[61]), "+f"(d[62]), "+f"(d[63]), "+f"(d[64]), "+f"(d[65]), "+f"(d[66]), "+f"(d[67]), "+f"(d[68]), "+f"(d[69]), "+f"(d[70]), "+f"(d[71]), "+f"(d[72]), "+f"(d[73]), "+f"(d[74]), "+f"(d[75]), "+f"(d[76]), "+f"(d[77]), "+f"(d[78]), "+f"(d[79]), "+f"(d[80]), "+f"(d[81]), "+f"(d[82]), "+f"(d[83]), "+f"(d[84]), "+f"(d[85]), "+f"(d[86]), "+f"(d[87]), "+f"(d[88]), "+f"(d[89]), "+f"(d[90]), "+f"(d[91]), "+f"(d[92]), "+f"(d[93]), "+f"(d[94]), "+f"(d[95])
    : "l"(da), "l"(db), "r"(scale_d));
}

__device__ __forceinline__ void wgmma_n192_rs(float (&d)[96], uint32_t a0, uint32_t a1, uint32_t a2, uint32_t a3, uint64_t db, int scale_d) {
  asm volatile("{\n.reg .pred p;\nsetp.ne.b32 p, %101, 0;\n"
    "wgmma.mma_async.sync.aligned.m64n192k16.f32.bf16.bf16 {%0, %1, %2, %3, %4, %5, %6, %7, %8, %9, %10, %11, %12, %13, %14, %15, %16, %17, %18, %19, %20, %21, %22, %23, %24, %25, %26, %27, %28, %29, %30, %31, %32, %33, %34, %35, %36, %37, %38, %39, %40, %41, %42, %43, %44, %45, %46, %47, %48, %49, %50, %51, %52, %53, %54, %55, %56, %57, %58, %59, %60, %61, %62, %63, %64, %65, %66, %67, %68, %69, %70, %71, %72, %73, %74, %75, %76, %77, %78, %79, %80, %81, %82, %83, %84, %85, %86, %87, %88, %89, %90, %91, %92, %93, %94, %95}, {%96, %97, %98, %99}, %100, p, 1, 1, 0;\n}\n"
    : "+f"(d[0]), "+f"(d[1]), "+f"(d[2]), "+f"(d[3]), "+f"(d[4]), "+f"(d[5]), "+f"(d[6]), "+f"(d[7]), "+f"(d[8]), "+f"(d[9]), "+f"(d[10]), "+f"(d[11]), "+f"(d[12]), "+f"(d[13]), "+f"(d[14]), "+f"(d[15]), "+f"(d[16]), "+f"(d[17]), "+f"(d[18]), "+f"(d[19]), "+f"(d[20]), "+f"(d[21]), "+f"(d[22]), "+f"(d[23]), "+f"(d[24]), "+f"(d[25]), "+f"(d[26]), "+f"(d[27]), "+f"(d[28]), "+f"(d[29]), "+f"(d[30]), "+f"(d[31]), "+f"(d[32]), "+f"(d[33]), "+f"(d[34]), "+f"(d[35]), "+f"(d[36]), "+f"(d[37]), "+f"(d[38]), "+f"(d[39]), "+f"(d[40]), "+f"(d[41]), "+f"(d[42]), "+f"(d[43]), "+f"(d[44]), "+f"(d[45]), "+f"(d[46]), "+f"(d[47]), "+f"(d[48]), "+f"(d[49]), "+f"(d[50]), "+f"(d[51]), "+f"(d[52]), "+f"(d[53]), "+f"(d[54]), "+f"(d[55]), "+f"(d[56]), "+f"(d[57]), "+f"(d[58]), "+f"(d[59]), "+f"(d[60]), "+f"(d[61]), "+f"(d[62]), "+f"(d[63]), "+f"(d[64]), "+f"(d[65]), "+f"(d[66]), "+f"(d[67]), "+f"(d[68]), "+f"(d[69]), "+f"(d[70]), "+f"(d[71]), "+f"(d[72]), "+f"(d[73]), "+f"(d[74]), "+f"(d[75]), "+f"(d[76]), "+f"(d[77]), "+f"(d[78]), "+f"(d[79]), "+f"(d[80]), "+f"(d[81]), "+f"(d[82]), "+f"(d[83]), "+f"(d[84]), "+f"(d[85]), "+f"(d[86]), "+f"(d[87]), "+f"(d[88]), "+f"(d[89]), "+f"(d[90]), "+f"(d[91]), "+f"(d[92]), "+f"(d[93]), "+f"(d[94]), "+f"(d[95])
    : "r"(a0), "r"(a1), "r"(a2), "r"(a3), "l"(db), "r"(scale_d));
}

__device__ __forceinline__ void wgmma_n192_rs_tb(float (&d)[96], uint32_t a0, uint32_t a1, uint32_t a2, uint32_t a3, uint64_t db, int scale_d) {
  asm volatile("{\n.reg .pred p;\nsetp.ne.b32 p, %101, 0;\n"
    "wgmma.mma_async.sync.aligned.m64n192k16.f32.bf16.bf16 {%0, %1, %2, %3, %4, %5, %6, %7, %8, %9, %10, %11, %12, %13, %14, %15, %16, %17, %18, %19, %20, %21, %22, %23, %24, %25, %26, %27, %28, %29, %30, %31, %32, %33, %34, %35, %36, %37, %38, %39, %40, %41, %42, %43, %44, %45, %46, %47, %48, %49, %50, %51, %52, %53, %54, %55, %56, %57, %58, %59, %60, %61, %62, %63, %64, %65, %66, %67, %68, %69, %70, %71, %72, %73, %74, %75, %76, %77, %78, %79, %80, %81, %82, %83, %84, %85, %86, %87, %88, %89, %90, %91, %92, %93, %94, %95}, {%96, %97, %98, %99}, %100, p, 1, 1, 1;\n}\n"
    : "+f"(d[0]), "+f"(d[1]), "+f"(d[2]), "+f"(d[3]), "+f"(d[4]), "+f"(d[5]), "+f"(d[6]), "+f"(d[7]), "+f"(d[8]), "+f"(d[9]), "+f"(d[10]), "+f"(d[11]), "+f"(d[12]), "+f"(d[13]), "+f"(d[14]), "+f"(d[15]), "+f"(d[16]), "+f"(d[17]), "+f"(d[18]), "+f"(d[19]), "+f"(d[20]), "+f"(d[21]), "+f"(d[22]), "+f"(d[23]), "+f"(d[24]), "+f"(d[25]), "+f"(d[26]), "+f"(d[27]), "+f"(d[28]), "+f"(d[29]), "+f"(d[30]), "+f"(d[31]), "+f"(d[32]), "+f"(d[33]), "+f"(d[34]), "+f"(d[35]), "+f"(d[36]), "+f"(d[37]), "+f"(d[38]), "+f"(d[39]), "+f"(d[40]), "+f"(d[41]), "+f"(d[42]), "+f"(d[43]), "+f"(d[44]), "+f"(d[45]), "+f"(d[46]), "+f"(d[47]), "+f"(d[48]), "+f"(d[49]), "+f"(d[50]), "+f"(d[51]), "+f"(d[52]), "+f"(d[53]), "+f"(d[54]), "+f"(d[55]), "+f"(d[56]), "+f"(d[57]), "+f"(d[58]), "+f"(d[59]), "+f"(d[60]), "+f"(d[61]), "+f"(d[62]), "+f"(d[63]), "+f"(d[64]), "+f"(d[65]), "+f"(d[66]), "+f"(d[67]), "+f"(d[68]), "+f"(d[69]), "+f"(d[70]), "+f"(d[71]), "+f"(d[72]), "+f"(d[73]), "+f"(d[74]), "+f"(d[75]), "+f"(d[76]), "+f"(d[77]), "+f"(d[78]), "+f"(d[79]), "+f"(d[80]), "+f"(d[81]), "+f"(d[82]), "+f"(d[83]), "+f"(d[84]), "+f"(d[85]), "+f"(d[86]), "+f"(d[87]), "+f"(d[88]), "+f"(d[89]), "+f"(d[90]), "+f"(d[91]), "+f"(d[92]), "+f"(d[93]), "+f"(d[94]), "+f"(d[95])
    : "r"(a0), "r"(a1), "r"(a2), "r"(a3), "l"(db), "r"(scale_d));
}

__device__ __forceinline__ void wgmma_n56_rs(float (&d)[28], uint32_t a0, uint32_t a1, uint32_t a2, uint32_t a3, uint64_t db, int scale_d) {
  asm volatile("{\n.reg .pred p;\nsetp.ne.b32 p, %33, 0;\n"
    "wgmma.mma_async.sync.aligned.m64n56k16.f32.bf16.bf16 {%0, %1, %2, %3, %4, %5, %6, %7, %8, %9, %10, %11, %12, %13, %14, %15, %16, %17, %18, %19, %20, %21, %22, %23, %24, %25, %26, %27}, {%28, %29, %30, %31}, %32, p, 1, 1, 0;\n}\n"
    : "+f"(d[0]), "+f"(d[1]), "+f"(d[2]), "+f"(d[3]), "+f"(d[4]), "+f"(d[5]), "+f"(d[6]), "+f"(d[7]), "+f"(d[8]), "+f"(d[9]), "+f"(d[10]), "+f"(d[11]), "+f"(d[12]), "+f"(d[13]), "+f"(d[14]), "+f"(d[15]), "+f"(d[16]), "+f"(d[17]), "+f"(d[18]), "+f"(d[19]), "+f"(d[20]), "+f"(d[21]), "+f"(d[22]), "+f"(d[23]), "+f"(d[24]), "+f"(d[25]), "+f"(d[26]), "+f"(d[27])
    : "r"(a0), "r"(a1), "r"(a2), "r"(a3), "l"(db), "r"(scale_d));
}

__device__ __forceinline__ void wgmma_n96_rs(float (&d)[48], uint32_t a0, uint32_t a1, uint32_t a2, uint32_t a3, uint64_t db, int scale_d) {
  asm volatile("{\n.reg .pred p;\nsetp.ne.b32 p, %53, 0;\n"
    "wgmma.mma_async.sync.aligned.m64n96k16.f32.bf16.bf16 {%0, %1, %2, %3, %4, %5, %6, %7, %8, %9, %10, %11, %12, %13, %14, %15, %16, %17, %18, %19, %20, %21, %22, %23, %24, %25, %26, %27, %28, %29, %30, %31, %32, %33, %34, %35, %36, %37, %38, %39, %40, %41, %42, %43, %44, %45, %46, %47}, {%48, %49, %50, %51}, %52, p, 1, 1, 0;\n}\n"
    : "+f"(d[0]), "+f"(d[1]), "+f"(d[2]), "+f"(d[3]), "+f"(d[4]), "+f"(d[5]), "+f"(d[6]), "+f"(d[7]), "+f"(d[8]), "+f"(d[9]), "+f"(d[10]), "+f"(d[11]), "+f"(d[12]), "+f"(d[13]), "+f"(d[14]), "+f"(d[15]), "+f"(d[16]), "+f"(d[17]), "+f"(d[18]), "+f"(d[19]), "+f"(d[20]), "+f"(d[21]), "+f"(d[22]), "+f"(d[23]), "+f"(d[24]), "+f"(d[25]), "+f"(d[26]), "+f"(d[27]), "+f"(d[28]), "+f"(d[29]), "+f"(d[30]), "+f"(d[31]), "+f"(d[32]), "+f"(d[33]), "+f"(d[34]), "+f"(d[35]), "+f"(d[36]), "+f"(d[37]), "+f"(d[38]), "+f"(d[39]), "+f"(d[40]), "+f"(d[41]), "+f"(d[42]), "+f"(d[43]), "+f"(d[44]), "+f"(d[45]), "+f"(d[46]), "+f"(d[47])
    : "r"(a0), "r"(a1), "r"(a2), "r"(a3), "l"(db), "r"(scale_d));
}

__device__ __forceinline__ void acc_fence(float (&d)[96]) {
  asm volatile("" : "+f"(d[0]), "+f"(d[1]), "+f"(d[2]), "+f"(d[3]), "+f"(d[4]), "+f"(d[5]), "+f"(d[6]), "+f"(d[7]), "+f"(d[8]), "+f"(d[9]), "+f"(d[10]), "+f"(d[11]), "+f"(d[12]), "+f"(d[13]), "+f"(d[14]), "+f"(d[15]), "+f"(d[16]), "+f"(d[17]), "+f"(d[18]), "+f"(d[19]), "+f"(d[20]), "+f"(d[21]), "+f"(d[22]), "+f"(d[23]), "+f"(d[24]), "+f"(d[25]), "+f"(d[26]), "+f"(d[27]), "+f"(d[28]), "+f"(d[29]), "+f"(d[30]), "+f"(d[31]), "+f"(d[32]), "+f"(d[33]), "+f"(d[34]), "+f"(d[35]), "+f"(d[36]), "+f"(d[37]), "+f"(d[38]), "+f"(d[39]), "+f"(d[40]), "+f"(d[41]), "+f"(d[42]), "+f"(d[43]), "+f"(d[44]), "+f"(d[45]), "+f"(d[46]), "+f"(d[47]), "+f"(d[48]), "+f"(d[49]), "+f"(d[50]), "+f"(d[51]), "+f"(d[52]), "+f"(d[53]), "+f"(d[54]), "+f"(d[55]), "+f"(d[56]), "+f"(d[57]), "+f"(d[58]), "+f"(d[59]), "+f"(d[60]), "+f"(d[61]), "+f"(d[62]), "+f"(d[63]), "+f"(d[64]), "+f"(d[65]), "+f"(d[66]), "+f"(d[67]), "+f"(d[68]), "+f"(d[69]), "+f"(d[70]), "+f"(d[71]), "+f"(d[72]), "+f"(d[73]), "+f"(d[74]), "+f"(d[75]), "+f"(d[76]), "+f"(d[77]), "+f"(d[78]), "+f"(d[79]), "+f"(d[80]), "+f"(d[81]), "+f"(d[82]), "+f"(d[83]), "+f"(d[84]), "+f"(d[85]), "+f"(d[86]), "+f"(d[87]), "+f"(d[88]), "+f"(d[89]), "+f"(d[90]), "+f"(d[91]), "+f"(d[92]), "+f"(d[93]), "+f"(d[94]), "+f"(d[95]) :: "memory");
}

__device__ __forceinline__ void acc_fence(float (&d)[28]) {
  asm volatile("" : "+f"(d[0]), "+f"(d[1]), "+f"(d[2]), "+f"(d[3]), "+f"(d[4]), "+f"(d[5]), "+f"(d[6]), "+f"(d[7]), "+f"(d[8]), "+f"(d[9]), "+f"(d[10]), "+f"(d[11]), "+f"(d[12]), "+f"(d[13]), "+f"(d[14]), "+f"(d[15]), "+f"(d[16]), "+f"(d[17]), "+f"(d[18]), "+f"(d[19]), "+f"(d[20]), "+f"(d[21]), "+f"(d[22]), "+f"(d[23]), "+f"(d[24]), "+f"(d[25]), "+f"(d[26]), "+f"(d[27]) :: "memory");
}

__device__ __forceinline__ void acc_fence(float (&d)[48]) {
  asm volatile("" : "+f"(d[0]), "+f"(d[1]), "+f"(d[2]), "+f"(d[3]), "+f"(d[4]), "+f"(d[5]), "+f"(d[6]), "+f"(d[7]), "+f"(d[8]), "+f"(d[9]), "+f"(d[10]), "+f"(d[11]), "+f"(d[12]), "+f"(d[13]), "+f"(d[14]), "+f"(d[15]), "+f"(d[16]), "+f"(d[17]), "+f"(d[18]), "+f"(d[19]), "+f"(d[20]), "+f"(d[21]), "+f"(d[22]), "+f"(d[23]), "+f"(d[24]), "+f"(d[25]), "+f"(d[26]), "+f"(d[27]), "+f"(d[28]), "+f"(d[29]), "+f"(d[30]), "+f"(d[31]), "+f"(d[32]), "+f"(d[33]), "+f"(d[34]), "+f"(d[35]), "+f"(d[36]), "+f"(d[37]), "+f"(d[38]), "+f"(d[39]), "+f"(d[40]), "+f"(d[41]), "+f"(d[42]), "+f"(d[43]), "+f"(d[44]), "+f"(d[45]), "+f"(d[46]), "+f"(d[47]) :: "memory");
}

constexpr int FW_LD = 200;
__global__ void __launch_bounds__(384) fold_weights_kernel(const __nv_bfloat16* __restrict__ wqkv_t, const __nv_bfloat16* __restrict__ wo_t,
                                    const __nv_bfloat16* __restrict__ wqkv_s, const __nv_bfloat16* __restrict__ wo_s) {
  extern __shared__ __align__(16) uint8_t fsm[];
  __nv_bfloat16* As = reinterpret_cast<__nv_bfloat16*>(fsm);
  float* part = reinterpret_cast<float*>(fsm + CH * FW_LD * 2);
  float* part2 = part + 16 * CH;
  float* cm = part2 + 16 * CH;
  float* Bs = cm + CH;
  const int mat = blockIdx.y, n0 = blockIdx.x * 16, tid = threadIdx.x;
  const __nv_bfloat16* wqkv = (mat < 2) ? wqkv_t : wqkv_s;
  const __nv_bfloat16* wo = (mat < 2) ? wo_t : wo_s;
  const bool isM = (mat & 1) == 0;
  const int offA = isM ? 0 : 2 * CH;
  const int cg = tid % 24, rg = tid / 24;
  {
    uint4 va[12], vb[12];
#pragma unroll
    for (int i = 0; i < 12; i++) va[i] = *reinterpret_cast<const uint4*>(wqkv + (rg * 12 + i) * 3 * CH + offA + cg * 8);
    if (isM) {
#pragma unroll
      for (int i = 0; i < 12; i++) vb[i] = *reinterpret_cast<const uint4*>(wqkv + (rg * 12 + i) * 3 * CH + CH + cg * 8);
    } else {
#pragma unroll
      for (int i = 0; i < 12; i++) vb[i] = make_uint4(0, 0, 0, 0);
    }
    float sa[8] = {0.f, 0.f, 0.f, 0.f, 0.f, 0.f, 0.f, 0.f}, sb[8] = {0.f, 0.f, 0.f, 0.f, 0.f, 0.f, 0.f, 0.f};
#pragma unroll
    for (int i = 0; i < 12; i++) {
      *reinterpret_cast<uint4*>(As + (rg * 12 + i) * FW_LD + cg * 8) = va[i];
      sa[0] += bf_lo(va[i].x); sa[1] += bf_hi(va[i].x); sa[2] += bf_lo(va[i].y); sa[3] += bf_hi(va[i].y);
      sa[4] += bf_lo(va[i].z); sa[5] += bf_hi(va[i].z); sa[6] += bf_lo(va[i].w); sa[7] += bf_hi(va[i].w);
      sb[0] += bf_lo(vb[i].x); sb[1] += bf_hi(vb[i].x); sb[2] += bf_lo(vb[i].y); sb[3] += bf_hi(vb[i].y);
      sb[4] += bf_lo(vb[i].z); sb[5] += bf_hi(vb[i].z); sb[6] += bf_lo(vb[i].w); sb[7] += bf_hi(vb[i].w);
    }
#pragma unroll
    for (int e = 0; e < 8; e++) { part[rg * CH + cg * 8 + e] = sa[e]; part2[rg * CH + cg * 8 + e] = sb[e]; }
  }
  __syncthreads();
  if (tid < CH) {
    float s = 0.f, s2 = 0.f;
#pragma unroll
    for (int r = 0; r < 16; r++) { s += part[r * CH + tid]; s2 += part2[r * CH + tid]; }
    cm[tid] = s * (1.0f / CH);
    const float cmB = s2 * (1.0f / CH);
#pragma unroll
    for (int n = 0; n < 16; n++)
      Bs[n * 196 + tid] = isM ? (__bfloat162float(wqkv[(n0 + n) * 3 * CH + CH + tid]) - cmB) : __bfloat162float(wo[tid * CH + n0 + n]);
  }
  __syncthreads();
  const int k = tid >> 1, nh = (tid & 1) * 8;
  float acc[8];
#pragma unroll
  for (int n = 0; n < 8; n++) acc[n] = 0.f;
#pragma unroll 4
  for (int c = 0; c < CH; c += 4) {
    const uint2 u = *reinterpret_cast<const uint2*>(As + k * FW_LD + c);
    const float4 m4 = *reinterpret_cast<const float4*>(cm + c);
    const float a0 = bf_lo(u.x) - m4.x, a1 = bf_hi(u.x) - m4.y, a2 = bf_lo(u.y) - m4.z, a3 = bf_hi(u.y) - m4.w;
#pragma unroll
    for (int n = 0; n < 8; n++) {
      const float4 b = *reinterpret_cast<const float4*>(Bs + (nh + n) * 196 + c);
      acc[n] = fmaf(a0, b.x, acc[n]); acc[n] = fmaf(a1, b.y, acc[n]);
      acc[n] = fmaf(a2, b.z, acc[n]); acc[n] = fmaf(a3, b.w, acc[n]);
    }
  }
  const int p = k >> 6, kc = k & 63;
#pragma unroll
  for (int n = 0; n < 8; n++) {
    const int nn = n0 + nh + n;
    g_w[mat][p * (CH * 64) + nn * 64 + (((kc >> 3) ^ (nn & 7)) << 3) + (kc & 7)] = __float2bfloat16(acc[n]);
  }
}
constexpr int FW_SMEM = CH * FW_LD * 2 + (32 * CH + CH + 16 * 196) * 4;

struct Params {
  int role;
};

__device__ __forceinline__ uint32_t frag_addr(uint32_t slot_rowoff, uint32_t sw, int hiblk, int kk) {
  const int ci = 2 * kk + hiblk;
  return slot_rowoff + (ci >> 3) * PANEL_X + ((((uint32_t)ci & 7u) ^ sw) << 4);
}

__device__ __forceinline__ float row_rstd(uint32_t slot, int w, int lane) {
  const int row = 16 * w + (lane >> 1), half = lane & 1;
  const uint32_t rbase = slot + row * 128, sw = row & 7;
  float s0 = 0.f, s1 = 0.f, s2 = 0.f, s3 = 0.f, q0 = 0.f, q1 = 0.f, q2 = 0.f, q3 = 0.f;
#pragma unroll
  for (int i = 0; i < 12; i++) {
    const int c = half * 12 + i;
    const uint4 v = lds128(rbase + (c >> 3) * PANEL_X + ((((uint32_t)c & 7u) ^ sw) << 4));
    float lo, hi;
    lo = bf_lo(v.x); hi = bf_hi(v.x); s0 += lo; s1 += hi; q0 = fmaf(lo, lo, q0); q1 = fmaf(hi, hi, q1);
    lo = bf_lo(v.y); hi = bf_hi(v.y); s2 += lo; s3 += hi; q2 = fmaf(lo, lo, q2); q3 = fmaf(hi, hi, q3);
    lo = bf_lo(v.z); hi = bf_hi(v.z); s0 += lo; s1 += hi; q0 = fmaf(lo, lo, q0); q1 = fmaf(hi, hi, q1);
    lo = bf_lo(v.w); hi = bf_hi(v.w); s2 += lo; s3 += hi; q2 = fmaf(lo, lo, q2); q3 = fmaf(hi, hi, q3);
  }
  float s = (s0 + s1) + (s2 + s3), ss = (q0 + q1) + (q2 + q3);
  s += __shfl_xor_sync(0xffffffffu, s, 1);
  ss += __shfl_xor_sync(0xffffffffu, ss, 1);
  const float mean = s * (1.0f / CH);
  const float var = fmaxf(ss * (1.0f / CH) - mean * mean, 0.f);
  return rsqrtf(var + 1e-5f);
}

__global__ void __launch_bounds__(NWG * 128 + 128, 1)
swin_main_kernel(const __grid_constant__ CUtensorMap map_in, const __grid_constant__ CUtensorMap map_out, const int role) {
  extern __shared__ __align__(1024) uint8_t smem_raw[];
  const uint32_t sbase = smem_u32(smem_raw);
  const int tid = threadIdx.x, wg = tid >> 7, t128 = tid & 127, w = t128 >> 5, lane = tid & 31;
  const int g = lane >> 2, q = lane & 3;

  const uint32_t bar_w = sbase + SMEM_MISC;
  float* rbuf = reinterpret_cast<float*>(smem_raw + SMEM_RBUF) + wg * 64;

  if (tid == 0) {
    mbar_init(bar_w, 1);
    for (int i = 0; i < NSLOT; i++) { mbar_init(sbase + SMEM_MISC + 8 + 8 * i, 1); mbar_init(sbase + SMEM_MISC + 64 + 8 * i, 128); }
    asm volatile("fence.mbarrier_init.release.cluster;" ::: "memory");
  }
  for (int i = tid; i < NSLOT * SLOT_BYTES / 16; i += NWG * 128 + 128)
    *reinterpret_cast<uint4*>(smem_raw + SMEM_SLOT + i * 16) = make_uint4(0, 0, 0, 0);
  fence_proxy_async();
  __syncthreads();

  const int nunits = role == 0 ? NTILE_A : NUNIT_B;
  const int ustride = gridDim.x;
  const int nj = (nunits - (int)blockIdx.x + ustride - 1) / ustride;
  const uint32_t tx_bytes = role == 0 ? SLOT_BYTES : 3 * 49 * 128;

  auto coords = [&](int j, int& c1, int& c2, int& c3) {
    const int u = blockIdx.x + j * ustride;
    if (role == 0) { c1 = 0; c2 = (u % 14) * 16; c3 = u / 14; }
    else { const int t = u & 3, wx = (u >> 2) & 31, wy = u >> 7; c1 = wx * 7; c2 = wy * 7; c3 = t; }
  };
  auto issue_load = [&](int j) {
    int c1, c2, c3; coords(j, c1, c2, c3);
    const int sl = j % NSLOT;
    const uint32_t bar = sbase + SMEM_MISC + 8 + 8 * sl;
    mbar_expect_tx(bar, tx_bytes);
#pragma unroll
    for (int p = 0; p < 3; p++) tma_load_4d(sbase + SMEM_SLOT + sl * SLOT_BYTES + p * PANEL_X, &map_in, p * 64, c1, c2, c3, bar);
  };
  auto prefetch_l2 = [&](int j) {
    if (j < nj) {
      int c1, c2, c3; coords(j, c1, c2, c3);
#pragma unroll
      for (int p = 0; p < 3; p++) tma_prefetch_4d(&map_in, p * 64, c1, c2, c3);
    }
  };

  if (tid >= NWG * 128) {
    asm volatile("setmaxnreg.dec.sync.aligned.u32 24;");
    if (tid == NWG * 128) {
      mbar_expect_tx(bar_w, 2 * WMAT_BYTES);
      bulk_load(sbase + SMEM_W0, &g_w[role * 2][0], WMAT_BYTES, bar_w);
      bulk_load(sbase + SMEM_W1, &g_w[role * 2 + 1][0], WMAT_BYTES, bar_w);
      for (int j = 0; j < NSLOT && j < nj; j++) issue_load(j);
      prefetch_l2(NSLOT); prefetch_l2(NSLOT + 1);
      for (int j = 0; j < nj; j++) {
        const int sl = j % NSLOT;
        mbar_wait(sbase + SMEM_MISC + 64 + 8 * sl, (j / NSLOT) & 1);
        int c1, c2, c3; coords(j, c1, c2, c3);
#pragma unroll
        for (int p = 0; p < 3; p++) tma_store_4d(&map_out, sbase + SMEM_SLOT + sl * SLOT_BYTES + p * PANEL_X, p * 64, c1, c2, c3);
        bulk_commit();
        bulk_wait_read0();
        if (j + NSLOT < nj) issue_load(j + NSLOT);
        prefetch_l2(j + NSLOT + 2);
      }
      bulk_wait0();
    }
    return;
  }
  asm volatile("setmaxnreg.inc.sync.aligned.u32 160;");
  mbar_wait(bar_w, 0);

  const int blk = lane >> 3;
  const int frow = 16 * w + (lane & 7) + ((blk & 1) << 3);
  const uint32_t fsw = frow & 7;
  const int fhi = blk >> 1;

  const uint64_t dW0 = make_desc(sbase + SMEM_W0, 16, 1024);
  const uint64_t dW1 = make_desc(sbase + SMEM_W1, 16, 1024);

  const float scale_l2e = 0.07216878364870322f * 1.4426950408889634f;

  for (int j = wg; j < nj; j += NWG) {
    const int sl = j % NSLOT;
    const uint32_t slot = sbase + SMEM_SLOT + sl * SLOT_BYTES;
    const uint32_t frowoff = slot + frow * 128;
    const uint64_t dX = make_desc(slot, 16, 1024);
    const uint64_t dXmn = make_desc(slot, PANEL_X, 1024);
    PH(0);
    mbar_wait(sbase + SMEM_MISC + 8 + 8 * sl, (j / NSLOT) & 1);
    PH(1);

    float acc[96];
    wgmma_fence();
#pragma unroll
    for (int kk = 0; kk < 12; kk++) {
      const uint32_t off = (kk >> 2) * PANEL_X + (kk & 3) * 32;
      const uint32_t offw = (kk >> 2) * PANEL_W + (kk & 3) * 32;
      wgmma_n192_ss(acc, dX + (off >> 4), dW0 + (offw >> 4), kk);
    }
    wgmma_commit();
    PH(2);
    const float rmine = row_rstd(slot, w, lane);
    PH(3);
    uint32_t fr[48];

    if (role == 0) {
      wgmma_wait0(); acc_fence(acc);
      PH(4);
#pragma unroll
      for (int i = 0; i < 48; i++) fr[i] = pack_bf16(acc[2 * i], acc[2 * i + 1]);
      float d0[4] = {0.f, 0.f, 0.f, 0.f}, d1[4] = {0.f, 0.f, 0.f, 0.f};
#pragma unroll
      for (int kk = 0; kk < 12; kk++) {
        uint32_t b0, b1, b2, b3;
        ldsm_x4(frag_addr(frowoff, fsw, fhi, kk), b0, b1, b2, b3);
        mma_16816(d0[0], d0[1], d0[2], d0[3], fr[4 * kk], fr[4 * kk + 1], fr[4 * kk + 2], fr[4 * kk + 3], b0, b2);
        mma_16816(d1[0], d1[1], d1[2], d1[3], fr[4 * kk], fr[4 * kk + 1], fr[4 * kk + 2], fr[4 * kk + 3], b1, b3);
      }
      const float rA = __shfl_sync(0xffffffffu, rmine, 2 * g);
      const float rB = __shfl_sync(0xffffffffu, rmine, 2 * g + 16);
      const float k0 = __shfl_sync(0xffffffffu, rmine, 4 * q);
      const float k1 = __shfl_sync(0xffffffffu, rmine, 4 * q + 2);
      const float k2 = __shfl_sync(0xffffffffu, rmine, 4 * q + 16);
      const float k3 = __shfl_sync(0xffffffffu, rmine, 4 * q + 18);
      const bool valid = (g >> 2) == (q >> 1);
      float sa0 = d0[0] * k0 * (rA * scale_l2e), sa1 = d0[1] * k1 * (rA * scale_l2e);
      float sb0 = d1[2] * k2 * (rB * scale_l2e), sb1 = d1[3] * k3 * (rB * scale_l2e);
      float ma = fmaxf(sa0, sa1), mb = fmaxf(sb0, sb1);
      ma = fmaxf(ma, __shfl_xor_sync(0xffffffffu, ma, 1));
      mb = fmaxf(mb, __shfl_xor_sync(0xffffffffu, mb, 1));
      const float ea0 = exp2f(sa0 - ma), ea1 = exp2f(sa1 - ma);
      const float eb0 = exp2f(sb0 - mb), eb1 = exp2f(sb1 - mb);
      float suma = ea0 + ea1, sumb = eb0 + eb1;
      suma += __shfl_xor_sync(0xffffffffu, suma, 1);
      sumb += __shfl_xor_sync(0xffffffffu, sumb, 1);
      const float ia = __fdividef(1.f, suma), ib = __fdividef(1.f, sumb);
      const uint32_t pa0 = valid ? pack_bf16(ea0 * ia * k0, ea1 * ia * k1) : 0u;
      const uint32_t pa3 = valid ? pack_bf16(eb0 * ib * k2, eb1 * ib * k3) : 0u;
      PH(5);
#pragma unroll
      for (int jj = 0; jj < 12; jj++) {
        uint32_t b0, b1, b2, b3;
        ldsm_x4_t(frag_addr(frowoff, fsw, fhi, jj), b0, b1, b2, b3);
        acc[8 * jj + 0] = 0.f; acc[8 * jj + 1] = 0.f; acc[8 * jj + 2] = 0.f; acc[8 * jj + 3] = 0.f;
        acc[8 * jj + 4] = 0.f; acc[8 * jj + 5] = 0.f; acc[8 * jj + 6] = 0.f; acc[8 * jj + 7] = 0.f;
        mma_16816(acc[8 * jj + 0], acc[8 * jj + 1], acc[8 * jj + 2], acc[8 * jj + 3], pa0, 0u, 0u, pa3, b0, b1);
        mma_16816(acc[8 * jj + 4], acc[8 * jj + 5], acc[8 * jj + 6], acc[8 * jj + 7], pa0, 0u, 0u, pa3, b2, b3);
      }
    } else {
      if ((lane & 1) == 0) rbuf[16 * w + (lane >> 1)] = rmine;
      wg_bar(1 + wg);
      wgmma_wait0(); acc_fence(acc);
      PH(4);
#pragma unroll
      for (int i = 0; i < 48; i++) fr[i] = pack_bf16(acc[2 * i], acc[2 * i + 1]);
      float s[28];
      wgmma_fence();
#pragma unroll
      for (int kk = 0; kk < 12; kk++) {
        const uint32_t off = (kk >> 2) * PANEL_X + (kk & 3) * 32;
        wgmma_n56_rs(s, fr[4 * kk], fr[4 * kk + 1], fr[4 * kk + 2], fr[4 * kk + 3], dX + (off >> 4), kk);
      }
      wgmma_commit();
      float rj[14];
#pragma unroll
      for (int j = 0; j < 7; j++) {
        const float2 v = *reinterpret_cast<const float2*>(&rbuf[8 * j + 2 * q]);
        rj[2 * j] = v.x; rj[2 * j + 1] = v.y;
      }
      const float ri0 = rbuf[16 * w + g] * scale_l2e, ri1 = rbuf[16 * w + g + 8] * scale_l2e;
      wgmma_wait0(); acc_fence(s);
      PH(5);
      float m0 = -INFINITY, m1 = -INFINITY;
#pragma unroll
      for (int j = 0; j < 7; j++) {
#pragma unroll
        for (int e = 0; e < 2; e++) {
          const bool ok = (j < 6) || (2 * q + e == 0);
          float v0 = s[4 * j + e] * rj[2 * j + e] * ri0;
          float v1 = s[4 * j + 2 + e] * rj[2 * j + e] * ri1;
          v0 = ok ? v0 : -INFINITY; v1 = ok ? v1 : -INFINITY;
          s[4 * j + e] = v0; s[4 * j + 2 + e] = v1;
          m0 = fmaxf(m0, v0); m1 = fmaxf(m1, v1);
        }
      }
      m0 = fmaxf(m0, __shfl_xor_sync(0xffffffffu, m0, 1)); m0 = fmaxf(m0, __shfl_xor_sync(0xffffffffu, m0, 2));
      m1 = fmaxf(m1, __shfl_xor_sync(0xffffffffu, m1, 1)); m1 = fmaxf(m1, __shfl_xor_sync(0xffffffffu, m1, 2));
      float sum0 = 0.f, sum1 = 0.f;
#pragma unroll
      for (int j = 0; j < 7; j++) {
#pragma unroll
        for (int e = 0; e < 2; e++) {
          const float e0 = exp2f(s[4 * j + e] - m0), e1 = exp2f(s[4 * j + 2 + e] - m1);
          s[4 * j + e] = e0; s[4 * j + 2 + e] = e1;
          sum0 += e0; sum1 += e1;
        }
      }
      sum0 += __shfl_xor_sync(0xffffffffu, sum0, 1); sum0 += __shfl_xor_sync(0xffffffffu, sum0, 2);
      sum1 += __shfl_xor_sync(0xffffffffu, sum1, 1); sum1 += __shfl_xor_sync(0xffffffffu, sum1, 2);
      const float i0 = __fdividef(1.f, sum0), i1 = __fdividef(1.f, sum1);
      uint32_t pa[16];
#pragma unroll
      for (int j = 0; j < 7; j++) {
        pa[(j >> 1) * 4 + (j & 1) * 2 + 0] = pack_bf16(s[4 * j] * i0 * rj[2 * j], s[4 * j + 1] * i0 * rj[2 * j + 1]);
        pa[(j >> 1) * 4 + (j & 1) * 2 + 1] = pack_bf16(s[4 * j + 2] * i1 * rj[2 * j], s[4 * j + 3] * i1 * rj[2 * j + 1]);
      }
      pa[14] = 0u; pa[15] = 0u;
      PH(6);
      wgmma_fence();
#pragma unroll
      for (int kk = 0; kk < 4; kk++)
        wgmma_n192_rs_tb(acc, pa[4 * kk], pa[4 * kk + 1], pa[4 * kk + 2], pa[4 * kk + 3], dXmn + ((kk * 2048) >> 4), kk);
      wgmma_commit();
      wgmma_wait0(); acc_fence(acc);
    }

    PH(7);
#pragma unroll
    for (int i = 0; i < 48; i++) fr[i] = pack_bf16(acc[2 * i], acc[2 * i + 1]);
#pragma unroll
    for (int hh = 0; hh < 2; hh++) {
      float o[48];
      wgmma_fence();
#pragma unroll
      for (int kk = 0; kk < 12; kk++) {
        const uint32_t offw = (kk >> 2) * PANEL_W + (kk & 3) * 32 + hh * (96 * 128);
        wgmma_n96_rs(o, fr[4 * kk], fr[4 * kk + 1], fr[4 * kk + 2], fr[4 * kk + 3], dW1 + (offw >> 4), kk);
      }
      wgmma_commit();
      wgmma_wait0(); acc_fence(o);
      if (hh == 0) { PH(8); wg_bar(1 + wg); PH(9); }
#pragma unroll
      for (int k6 = 0; k6 < 6; k6++) {
        const uint32_t a = frag_addr(frowoff, fsw, fhi, hh * 6 + k6);
        uint32_t x0, x1, x2, x3;
        ldsm_x4(a, x0, x1, x2, x3);
        const uint32_t o0 = add_bf16x2(x0, pack_bf16(o[8 * k6 + 0], o[8 * k6 + 1]));
        const uint32_t o1 = add_bf16x2(x1, pack_bf16(o[8 * k6 + 2], o[8 * k6 + 3]));
        const uint32_t o2 = add_bf16x2(x2, pack_bf16(o[8 * k6 + 4], o[8 * k6 + 5]));
        const uint32_t o3 = add_bf16x2(x3, pack_bf16(o[8 * k6 + 6], o[8 * k6 + 7]));
        stsm_x4(a, o0, o1, o2, o3);
      }
    }
    PH(10);
    fence_proxy_async();
    mbar_arrive(sbase + SMEM_MISC + 64 + 8 * sl);
    PH(11);
  }
}

typedef CUresult (*EncodeTiledFn)(CUtensorMap*, CUtensorMapDataType, cuuint32_t, void*, const cuuint64_t*, const cuuint64_t*,
                                  const cuuint32_t*, const cuuint32_t*, CUtensorMapInterleave, CUtensorMapSwizzle,
                                  CUtensorMapL2promotion, CUtensorMapFloatOOBfill);

bool make_map(EncodeTiledFn fn, CUtensorMap* m, void* base, bool pixel_major) {
  cuuint64_t dims[4]; cuuint64_t strides[3]; cuuint32_t box[4]; cuuint32_t es[4] = {1, 1, 1, 1};
  const cuuint64_t sC = (cuuint64_t)CH * 2, sW = sC * WW, sT = sW * HH;
  if (pixel_major) {
    dims[0] = CH; dims[1] = TT; dims[2] = WW; dims[3] = HH;
    strides[0] = sT; strides[1] = sC; strides[2] = sW;
    box[0] = 64; box[1] = 4; box[2] = 16; box[3] = 1;
  } else {
    dims[0] = CH; dims[1] = WW; dims[2] = HH; dims[3] = TT;
    strides[0] = sC; strides[1] = sW; strides[2] = sT;
    box[0] = 64; box[1] = 7; box[2] = 7; box[3] = 1;
  }
  return fn(m, CU_TENSOR_MAP_DATA_TYPE_BFLOAT16, 4, base, dims, strides, box, es, CU_TENSOR_MAP_INTERLEAVE_NONE,
            CU_TENSOR_MAP_SWIZZLE_128B, CU_TENSOR_MAP_L2_PROMOTION_L2_256B, CU_TENSOR_MAP_FLOAT_OOB_FILL_NONE) == CUDA_SUCCESS;
}

}

extern "C" void kernel_launch(void* const* d_in, const int* in_sizes, int n_in, void* d_out, int out_size) {
  const __nv_bfloat16* x = (const __nv_bfloat16*)d_in[0];
  const __nv_bfloat16* wqkv_t = (const __nv_bfloat16*)d_in[1];
  const __nv_bfloat16* wo_t = (const __nv_bfloat16*)d_in[2];
  const __nv_bfloat16* wqkv_s = (const __nv_bfloat16*)d_in[3];
  const __nv_bfloat16* wo_s = (const __nv_bfloat16*)d_in[4];

  static bool init = false;
  static CUtensorMap mA_in, mA_out, mB_in, mB_out;
  static void* last_x = nullptr; static void* last_out = nullptr;
  static int nsm = 132;
  if (!init || last_x != d_in[0] || last_out != d_out) {
    void* fnp = nullptr; cudaDriverEntryPointQueryResult qr;
    cudaGetDriverEntryPoint("cuTensorMapEncodeTiled", &fnp, cudaEnableDefault, &qr);
    EncodeTiledFn fn = (EncodeTiledFn)fnp;
    void* x1p = nullptr; cudaGetSymbolAddress(&x1p, g_x1);
    make_map(fn, &mA_in, (void*)x, true);
    make_map(fn, &mA_out, x1p, true);
    make_map(fn, &mB_in, x1p, false);
    make_map(fn, &mB_out, d_out, false);
    cudaFuncSetAttribute(fold_weights_kernel, cudaFuncAttributeMaxDynamicSharedMemorySize, FW_SMEM);
    cudaFuncSetAttribute(swin_main_kernel, cudaFuncAttributeMaxDynamicSharedMemorySize, SMEM_TOTAL);
    cudaDeviceGetAttribute(&nsm, cudaDevAttrMultiProcessorCount, 0);
    init = true; last_x = d_in[0]; last_out = d_out;
  }
  fold_weights_kernel<<<dim3(12, 4), 384, FW_SMEM>>>(wqkv_t, wo_t, wqkv_s, wo_s);
  swin_main_kernel<<<nsm, NWG * 128 + 128, SMEM_TOTAL>>>(mA_in, mA_out, 0);
  swin_main_kernel<<<nsm, NWG * 128 + 128, SMEM_TOTAL>>>(mB_in, mB_out, 1);
}
```

```cpp
#include <cuda_runtime.h>
#include <cuda_bf16.h>
#include <cuda.h>
#include <stdint.h>

namespace {

constexpr int CH = 192;
constexpr int TT = 4, HH = 224, WW = 224;
constexpr int NTOK = TT * HH * WW;
constexpr int PANEL_X = 64 * 128;
constexpr int SLOT_BYTES = 3 * PANEL_X;
constexpr int PANEL_W = 192 * 128;
constexpr int WMAT_BYTES = 3 * PANEL_W;
constexpr int NWG = 2;
constexpr int NSLOT = 3;
constexpr int SMEM_W0 = 0;
constexpr int SMEM_W1 = WMAT_BYTES;
constexpr int SMEM_SLOT = 2 * WMAT_BYTES;
constexpr int SMEM_MISC = SMEM_SLOT + NSLOT * SLOT_BYTES;
constexpr int SMEM_RBUF = SMEM_MISC + 128;
constexpr int SMEM_TOTAL = SMEM_RBUF + NWG * 64 * 4;

constexpr int NTILE_A = HH * (WW / 16);
constexpr int NUNIT_B = 32 * 32 * 4;

__device__ __nv_bfloat16 g_x1[(size_t)NTOK * CH];
__device__ __align__(1024) __nv_bfloat16 g_w[4][CH * CH];

#define PH(i) do {} while (0)
__device__ __forceinline__ uint32_t smem_u32(const void* p) { return (uint32_t)__cvta_generic_to_shared(p); }

__device__ __forceinline__ void mbar_init(uint32_t bar, uint32_t count) {
  asm volatile("mbarrier.init.shared::cta.b64 [%0], %1;" :: "r"(bar), "r"(count));
}
__device__ __forceinline__ void mbar_expect_tx(uint32_t bar, uint32_t bytes) {
  asm volatile("mbarrier.arrive.expect_tx.shared::cta.b64 _, [%0], %1;" :: "r"(bar), "r"(bytes) : "memory");
}
__device__ __forceinline__ void mbar_arrive(uint32_t bar) {
  asm volatile("mbarrier.arrive.shared::cta.b64 _, [%0];" :: "r"(bar) : "memory");
}
__device__ __forceinline__ void mbar_wait(uint32_t bar, uint32_t parity) {
  asm volatile(
    "{\n.reg .pred p;\n"
    "WAIT_%=:\n"
    "mbarrier.try_wait.parity.shared::cta.b64 p, [%0], %1;\n"
    "@p bra DONE_%=;\n"
    "bra WAIT_%=;\n"
    "DONE_%=:\n}\n" :: "r"(bar), "r"(parity) : "memory");
}
__device__ __forceinline__ void tma_load_4d(uint32_t dst, const CUtensorMap* map, int c0, int c1, int c2, int c3, uint32_t bar) {
  asm volatile("cp.async.bulk.tensor.4d.shared::cluster.global.tile.mbarrier::complete_tx::bytes [%0], [%1, {%2, %3, %4, %5}], [%6];"
    :: "r"(dst), "l"(map), "r"(c0), "r"(c1), "r"(c2), "r"(c3), "r"(bar) : "memory");
}
__device__ __forceinline__ void tma_prefetch_4d(const CUtensorMap* map, int c0, int c1, int c2, int c3) {
  asm volatile("cp.async.bulk.prefetch.tensor.4d.L2.global.tile [%0, {%1, %2, %3, %4}];"
    :: "l"(map), "r"(c0), "r"(c1), "r"(c2), "r"(c3) : "memory");
}
__device__ __forceinline__ void tma_store_4d(const CUtensorMap* map, uint32_t src, int c0, int c1, int c2, int c3) {
  asm volatile("cp.async.bulk.tensor.4d.global.shared::cta.tile.bulk_group [%0, {%1, %2, %3, %4}], [%5];"
    :: "l"(map), "r"(c0), "r"(c1), "r"(c2), "r"(c3), "r"(src) : "memory");
}
__device__ __forceinline__ void bulk_load(uint32_t dst, const void* src, uint32_t bytes, uint32_t bar) {
  asm volatile("cp.async.bulk.shared::cluster.global.mbarrier::complete_tx::bytes [%0], [%1], %2, [%3];"
    :: "r"(dst), "l"(src), "r"(bytes), "r"(bar) : "memory");
}
__device__ __forceinline__ void bulk_commit() { asm volatile("cp.async.bulk.commit_group;" ::: "memory"); }
__device__ __forceinline__ void bulk_wait_read0() { asm volatile("cp.async.bulk.wait_group.read 0;" ::: "memory"); }
__device__ __forceinline__ void bulk_wait0() { asm volatile("cp.async.bulk.wait_group 0;" ::: "memory"); }
__device__ __forceinline__ void fence_proxy_async() { asm volatile("fence.proxy.async.shared::cta;" ::: "memory"); }
__device__ __forceinline__ void wg_bar(int id) { asm volatile("bar.sync %0, 128;" :: "r"(id) : "memory"); }
__device__ __forceinline__ void wgmma_fence() { asm volatile("wgmma.fence.sync.aligned;" ::: "memory"); }
__device__ __forceinline__ void wgmma_commit() { asm volatile("wgmma.commit_group.sync.aligned;" ::: "memory"); }
__device__ __forceinline__ void wgmma_wait0() { asm volatile("wgmma.wait_group.sync.aligned 0;" ::: "memory"); }

__device__ __forceinline__ uint64_t make_desc(uint32_t saddr, uint32_t lbo, uint32_t sbo) {
  return (uint64_t)((saddr & 0x3FFFF) >> 4) | ((uint64_t)((lbo & 0x3FFFF) >> 4) << 16) |
         ((uint64_t)((sbo & 0x3FFFF) >> 4) << 32) | ((uint64_t)1 << 62);
}
__device__ __forceinline__ uint32_t pack_bf16(float lo, float hi) {
  uint32_t r; asm("cvt.rn.bf16x2.f32 %0, %1, %2;" : "=r"(r) : "f"(hi), "f"(lo)); return r;
}
__device__ __forceinline__ uint32_t add_bf16x2(uint32_t a, uint32_t b) {
  uint32_t r; asm("add.rn.bf16x2 %0, %1, %2;" : "=r"(r) : "r"(a), "r"(b)); return r;
}
__device__ __forceinline__ float bf_lo(uint32_t u) { return __uint_as_float(u << 16); }
__device__ __forceinline__ float bf_hi(uint32_t u) { return __uint_as_float(u & 0xffff0000u); }
__device__ __forceinline__ void ldsm_x4(uint32_t addr, uint32_t& r0, uint32_t& r1, uint32_t& r2, uint32_t& r3) {
  asm volatile("ldmatrix.sync.aligned.m8n8.x4.shared.b16 {%0,%1,%2,%3}, [%4];"
    : "=r"(r0), "=r"(r1), "=r"(r2), "=r"(r3) : "r"(addr) : "memory");
}
__device__ __forceinline__ void ldsm_x4_t(uint32_t addr, uint32_t& r0, uint32_t& r1, uint32_t& r2, uint32_t& r3) {
  asm volatile("ldmatrix.sync.aligned.m8n8.x4.trans.shared.b16 {%0,%1,%2,%3}, [%4];"
    : "=r"(r0), "=r"(r1), "=r"(r2), "=r"(r3) : "r"(addr) : "memory");
}
__device__ __forceinline__ void stsm_x4(uint32_t addr, uint32_t r0, uint32_t r1, uint32_t r2, uint32_t r3) {
  asm volatile("stmatrix.sync.aligned.m8n8.x4.shared.b16 [%0], {%1,%2,%3,%4};"
    :: "r"(addr), "r"(r0), "r"(r1), "r"(r2), "r"(r3) : "memory");
}
__device__ __forceinline__ void mma_16816(float& d0, float& d1, float& d2, float& d3,
                                          uint32_t a0, uint32_t a1, uint32_t a2, uint32_t a3, uint32_t b0, uint32_t b1) {
  asm volatile("mma.sync.aligned.m16n8k16.row.col.f32.bf16.bf16.f32 {%0,%1,%2,%3}, {%4,%5,%6,%7}, {%8,%9}, {%0,%1,%2,%3};"
    : "+f"(d0), "+f"(d1), "+f"(d2), "+f"(d3) : "r"(a0), "r"(a1), "r"(a2), "r"(a3), "r"(b0), "r"(b1));
}
__device__ __forceinline__ uint4 lds128(uint32_t addr) {
  uint4 v; asm volatile("ld.shared.v4.u32 {%0,%1,%2,%3}, [%4];" : "=r"(v.x), "=r"(v.y), "=r"(v.z), "=r"(v.w) : "r"(addr) : "memory");
  return v;
}

__device__ __forceinline__ void wgmma_n192_ss(float (&d)[96], uint64_t da, uint64_t db, int scale_d) {
  asm volatile("{\n.reg .pred p;\nsetp.ne.b32 p, %98, 0;\n"
    "wgmma.mma_async.sync.aligned.m64n192k16.f32.bf16.bf16 {%0, %1, %2, %3, %4, %5, %6, %7, %8, %9, %10, %11, %12, %13, %14, %15, %16, %17, %18, %19, %20, %21, %22, %23, %24, %25, %26, %27, %28, %29, %30, %31, %32, %33, %34, %35, %36, %37, %38, %39, %40, %41, %42, %43, %44, %45, %46, %47, %48, %49, %50, %51, %52, %53, %54, %55, %56, %57, %58, %59, %60, %61, %62, %63, %64, %65, %66, %67, %68, %69, %70, %71, %72, %73, %74, %75, %76, %77, %78, %79, %80, %81, %82, %83, %84, %85, %86, %87, %88, %89, %90, %91, %92, %93, %94, %95}, %96, %97, p, 1, 1, 0, 0;\n}\n"
    : "+f"(d[0]), "+f"(d[1]), "+f"(d[2]), "+f"(d[3]), "+f"(d[4]), "+f"(d[5]), "+f"(d[6]), "+f"(d[7]), "+f"(d[8]), "+f"(d[9]), "+f"(d[10]), "+f"(d[11]), "+f"(d[12]), "+f"(d[13]), "+f"(d[14]), "+f"(d[15]), "+f"(d[16]), "+f"(d[17]), "+f"(d[18]), "+f"(d[19]), "+f"(d[20]), "+f"(d[21]), "+f"(d[22]), "+f"(d[23]), "+f"(d[24]), "+f"(d[25]), "+f"(d[26]), "+f"(d[27]), "+f"(d[28]), "+f"(d[29]), "+f"(d[30]), "+f"(d[31]), "+f"(d[32]), "+f"(d[33]), "+f"(d[34]), "+f"(d[35]), "+f"(d[36]), "+f"(d[37]), "+f"(d[38]), "+f"(d[39]), "+f"(d[40]), "+f"(d[41]), "+f"(d[42]), "+f"(d[43]), "+f"(d[44]), "+f"(d[45]), "+f"(d[46]), "+f"(d[47]), "+f"(d[48]), "+f"(d[49]), "+f"(d[50]), "+f"(d[51]), "+f"(d[52]), "+f"(d[53]), "+f"(d[54]), "+f"(d[55]), "+f"(d[56]), "+f"(d[57]), "+f"(d[58]), "+f"(d[59]), "+f"(d[60]), "+f"(d[61]), "+f"(d[62]), "+f"(d[63]), "+f"(d[64]), "+f"(d[65]), "+f"(d[66]), "+f"(d[67]), "+f"(d[68]), "+f"(d[69]), "+f"(d[70]), "+f"(d[71]), "+f"(d[72]), "+f"(d[73]), "+f"(d[74]), "+f"(d[75]), "+f"(d[76]), "+f"(d[77]), "+f"(d[78]), "+f"(d[79]), "+f"(d[80]), "+f"(d[81]), "+f"(d[82]), "+f"(d[83]), "+f"(d[84]), "+f"(d[85]), "+f"(d[86]), "+f"(d[87]), "+f"(d[88]), "+f"(d[89]), "+f"(d[90]), "+f"(d[91]), "+f"(d[92]), "+f"(d[93]), "+f"(d[94]), "+f"(d[95])
    : "l"(da), "l"(db), "r"(scale_d));
}

__device__ __forceinline__ void wgmma_n192_rs(float (&d)[96], uint32_t a0, uint32_t a1, uint32_t a2, uint32_t a3, uint64_t db, int scale_d) {
  asm volatile("{\n.reg .pred p;\nsetp.ne.b32 p, %101, 0;\n"
    "wgmma.mma_async.sync.aligned.m64n192k16.f32.bf16.bf16 {%0, %1, %2, %3, %4, %5, %6, %7, %8, %9, %10, %11, %12, %13, %14, %15, %16, %17, %18, %19, %20, %21, %22, %23, %24, %25, %26, %27, %28, %29, %30, %31, %32, %33, %34, %35, %36, %37, %38, %39, %40, %41, %42, %43, %44, %45, %46, %47, %48, %49, %50, %51, %52, %53, %54, %55, %56, %57, %58, %59, %60, %61, %62, %63, %64, %65, %66, %67, %68, %69, %70, %71, %72, %73, %74, %75, %76, %77, %78, %79, %80, %81, %82, %83, %84, %85, %86, %87, %88, %89, %90, %91, %92, %93, %94, %95}, {%96, %97, %98, %99}, %100, p, 1, 1, 0;\n}\n"
    : "+f"(d[0]), "+f"(d[1]), "+f"(d[2]), "+f"(d[3]), "+f"(d[4]), "+f"(d[5]), "+f"(d[6]), "+f"(d[7]), "+f"(d[8]), "+f"(d[9]), "+f"(d[10]), "+f"(d[11]), "+f"(d[12]), "+f"(d[13]), "+f"(d[14]), "+f"(d[15]), "+f"(d[16]), "+f"(d[17]), "+f"(d[18]), "+f"(d[19]), "+f"(d[20]), "+f"(d[21]), "+f"(d[22]), "+f"(d[23]), "+f"(d[24]), "+f"(d[25]), "+f"(d[26]), "+f"(d[27]), "+f"(d[28]), "+f"(d[29]), "+f"(d[30]), "+f"(d[31]), "+f"(d[32]), "+f"(d[33]), "+f"(d[34]), "+f"(d[35]), "+f"(d[36]), "+f"(d[37]), "+f"(d[38]), "+f"(d[39]), "+f"(d[40]), "+f"(d[41]), "+f"(d[42]), "+f"(d[43]), "+f"(d[44]), "+f"(d[45]), "+f"(d[46]), "+f"(d[47]), "+f"(d[48]), "+f"(d[49]), "+f"(d[50]), "+f"(d[51]), "+f"(d[52]), "+f"(d[53]), "+f"(d[54]), "+f"(d[55]), "+f"(d[56]), "+f"(d[57]), "+f"(d[58]), "+f"(d[59]), "+f"(d[60]), "+f"(d[61]), "+f"(d[62]), "+f"(d[63]), "+f"(d[64]), "+f"(d[65]), "+f"(d[66]), "+f"(d[67]), "+f"(d[68]), "+f"(d[69]), "+f"(d[70]), "+f"(d[71]), "+f"(d[72]), "+f"(d[73]), "+f"(d[74]), "+f"(d[75]), "+f"(d[76]), "+f"(d[77]), "+f"(d[78]), "+f"(d[79]), "+f"(d[80]), "+f"(d[81]), "+f"(d[82]), "+f"(d[83]), "+f"(d[84]), "+f"(d[85]), "+f"(d[86]), "+f"(d[87]), "+f"(d[88]), "+f"(d[89]), "+f"(d[90]), "+f"(d[91]), "+f"(d[92]), "+f"(d[93]), "+f"(d[94]), "+f"(d[95])
    : "r"(a0), "r"(a1), "r"(a2), "r"(a3), "l"(db), "r"(scale_d));
}

__device__ __forceinline__ void wgmma_n192_rs_tb(float (&d)[96], uint32_t a0, uint32_t a1, uint32_t a2, uint32_t a3, uint64_t db, int scale_d) {
  asm volatile("{\n.reg .pred p;\nsetp.ne.b32 p, %101, 0;\n"
    "wgmma.mma_async.sync.aligned.m64n192k16.f32.bf16.bf16 {%0, %1, %2, %3, %4, %5, %6, %7, %8, %9, %10, %11, %12, %13, %14, %15, %16, %17, %18, %19, %20, %21, %22, %23, %24, %25, %26, %27, %28, %29, %30, %31, %32, %33, %34, %35, %36, %37, %38, %39, %40, %41, %42, %43, %44, %45, %46, %47, %48, %49, %50, %51, %52, %53, %54, %55, %56, %57, %58, %59, %60, %61, %62, %63, %64, %65, %66, %67, %68, %69, %70, %71, %72, %73, %74, %75, %76, %77, %78, %79, %80, %81, %82, %83, %84, %85, %86, %87, %88, %89, %90, %91, %92, %93, %94, %95}, {%96, %97, %98, %99}, %100, p, 1, 1, 1;\n}\n"
    : "+f"(d[0]), "+f"(d[1]), "+f"(d[2]), "+f"(d[3]), "+f"(d[4]), "+f"(d[5]), "+f"(d[6]), "+f"(d[7]), "+f"(d[8]), "+f"(d[9]), "+f"(d[10]), "+f"(d[11]), "+f"(d[12]), "+f"(d[13]), "+f"(d[14]), "+f"(d[15]), "+f"(d[16]), "+f"(d[17]), "+f"(d[18]), "+f"(d[19]), "+f"(d[20]), "+f"(d[21]), "+f"(d[22]), "+f"(d[23]), "+f"(d[24]), "+f"(d[25]), "+f"(d[26]), "+f"(d[27]), "+f"(d[28]), "+f"(d[29]), "+f"(d[30]), "+f"(d[31]), "+f"(d[32]), "+f"(d[33]), "+f"(d[34]), "+f"(d[35]), "+f"(d[36]), "+f"(d[37]), "+f"(d[38]), "+f"(d[39]), "+f"(d[40]), "+f"(d[41]), "+f"(d[42]), "+f"(d[43]), "+f"(d[44]), "+f"(d[45]), "+f"(d[46]), "+f"(d[47]), "+f"(d[48]), "+f"(d[49]), "+f"(d[50]), "+f"(d[51]), "+f"(d[52]), "+f"(d[53]), "+f"(d[54]), "+f"(d[55]), "+f"(d[56]), "+f"(d[57]), "+f"(d[58]), "+f"(d[59]), "+f"(d[60]), "+f"(d[61]), "+f"(d[62]), "+f"(d[63]), "+f"(d[64]), "+f"(d[65]), "+f"(d[66]), "+f"(d[67]), "+f"(d[68]), "+f"(d[69]), "+f"(d[70]), "+f"(d[71]), "+f"(d[72]), "+f"(d[73]), "+f"(d[74]), "+f"(d[75]), "+f"(d[76]), "+f"(d[77]), "+f"(d[78]), "+f"(d[79]), "+f"(d[80]), "+f"(d[81]), "+f"(d[82]), "+f"(d[83]), "+f"(d[84]), "+f"(d[85]), "+f"(d[86]), "+f"(d[87]), "+f"(d[88]), "+f"(d[89]), "+f"(d[90]), "+f"(d[91]), "+f"(d[92]), "+f"(d[93]), "+f"(d[94]), "+f"(d[95])
    : "r"(a0), "r"(a1), "r"(a2), "r"(a3), "l"(db), "r"(scale_d));
}

__device__ __forceinline__ void wgmma_n56_rs(float (&d)[28], uint32_t a0, uint32_t a1, uint32_t a2, uint32_t a3, uint64_t db, int scale_d) {
  asm volatile("{\n.reg .pred p;\nsetp.ne.b32 p, %33, 0;\n"
    "wgmma.mma_async.sync.aligned.m64n56k16.f32.bf16.bf16 {%0, %1, %2, %3, %4, %5, %6, %7, %8, %9, %10, %11, %12, %13, %14, %15, %16, %17, %18, %19, %20, %21, %22, %23, %24, %25, %26, %27}, {%28, %29, %30, %31}, %32, p, 1, 1, 0;\n}\n"
    : "+f"(d[0]), "+f"(d[1]), "+f"(d[2]), "+f"(d[3]), "+f"(d[4]), "+f"(d[5]), "+f"(d[6]), "+f"(d[7]), "+f"(d[8]), "+f"(d[9]), "+f"(d[10]), "+f"(d[11]), "+f"(d[12]), "+f"(d[13]), "+f"(d[14]), "+f"(d[15]), "+f"(d[16]), "+f"(d[17]), "+f"(d[18]), "+f"(d[19]), "+f"(d[20]), "+f"(d[21]), "+f"(d[22]), "+f"(d[23]), "+f"(d[24]), "+f"(d[25]), "+f"(d[26]), "+f"(d[27])
    : "r"(a0), "r"(a1), "r"(a2), "r"(a3), "l"(db), "r"(scale_d));
}

__device__ __forceinline__ void wgmma_n96_rs(float (&d)[48], uint32_t a0, uint32_t a1, uint32_t a2, uint32_t a3, uint64_t db, int scale_d) {
  asm volatile("{\n.reg .pred p;\nsetp.ne.b32 p, %53, 0;\n"
    "wgmma.mma_async.sync.aligned.m64n96k16.f32.bf16.bf16 {%0, %1, %2, %3, %4, %5, %6, %7, %8, %9, %10, %11, %12, %13, %14, %15, %16, %17, %18, %19, %20, %21, %22, %23, %24, %25, %26, %27, %28, %29, %30, %31, %32, %33, %34, %35, %36, %37, %38, %39, %40, %41, %42, %43, %44, %45, %46, %47}, {%48, %49, %50, %51}, %52, p, 1, 1, 0;\n}\n"
    : "+f"(d[0]), "+f"(d[1]), "+f"(d[2]), "+f"(d[3]), "+f"(d[4]), "+f"(d[5]), "+f"(d[6]), "+f"(d[7]), "+f"(d[8]), "+f"(d[9]), "+f"(d[10]), "+f"(d[11]), "+f"(d[12]), "+f"(d[13]), "+f"(d[14]), "+f"(d[15]), "+f"(d[16]), "+f"(d[17]), "+f"(d[18]), "+f"(d[19]), "+f"(d[20]), "+f"(d[21]), "+f"(d[22]), "+f"(d[23]), "+f"(d[24]), "+f"(d[25]), "+f"(d[26]), "+f"(d[27]), "+f"(d[28]), "+f"(d[29]), "+f"(d[30]), "+f"(d[31]), "+f"(d[32]), "+f"(d[33]), "+f"(d[34]), "+f"(d[35]), "+f"(d[36]), "+f"(d[37]), "+f"(d[38]), "+f"(d[39]), "+f"(d[40]), "+f"(d[41]), "+f"(d[42]), "+f"(d[43]), "+f"(d[44]), "+f"(d[45]), "+f"(d[46]), "+f"(d[47])
    : "r"(a0), "r"(a1), "r"(a2), "r"(a3), "l"(db), "r"(scale_d));
}

__device__ __forceinline__ void acc_fence(float (&d)[96]) {
  asm volatile("" : "+f"(d[0]), "+f"(d[1]), "+f"(d[2]), "+f"(d[3]), "+f"(d[4]), "+f"(d[5]), "+f"(d[6]), "+f"(d[7]), "+f"(d[8]), "+f"(d[9]), "+f"(d[10]), "+f"(d[11]), "+f"(d[12]), "+f"(d[13]), "+f"(d[14]), "+f"(d[15]), "+f"(d[16]), "+f"(d[17]), "+f"(d[18]), "+f"(d[19]), "+f"(d[20]), "+f"(d[21]), "+f"(d[22]), "+f"(d[23]), "+f"(d[24]), "+f"(d[25]), "+f"(d[26]), "+f"(d[27]), "+f"(d[28]), "+f"(d[29]), "+f"(d[30]), "+f"(d[31]), "+f"(d[32]), "+f"(d[33]), "+f"(d[34]), "+f"(d[35]), "+f"(d[36]), "+f"(d[37]), "+f"(d[38]), "+f"(d[39]), "+f"(d[40]), "+f"(d[41]), "+f"(d[42]), "+f"(d[43]), "+f"(d[44]), "+f"(d[45]), "+f"(d[46]), "+f"(d[47]), "+f"(d[48]), "+f"(d[49]), "+f"(d[50]), "+f"(d[51]), "+f"(d[52]), "+f"(d[53]), "+f"(d[54]), "+f"(d[55]), "+f"(d[56]), "+f"(d[57]), "+f"(d[58]), "+f"(d[59]), "+f"(d[60]), "+f"(d[61]), "+f"(d[62]), "+f"(d[63]), "+f"(d[64]), "+f"(d[65]), "+f"(d[66]), "+f"(d[67]), "+f"(d[68]), "+f"(d[69]), "+f"(d[70]), "+f"(d[71]), "+f"(d[72]), "+f"(d[73]), "+f"(d[74]), "+f"(d[75]), "+f"(d[76]), "+f"(d[77]), "+f"(d[78]), "+f"(d[79]), "+f"(d[80]), "+f"(d[81]), "+f"(d[82]), "+f"(d[83]), "+f"(d[84]), "+f"(d[85]), "+f"(d[86]), "+f"(d[87]), "+f"(d[88]), "+f"(d[89]), "+f"(d[90]), "+f"(d[91]), "+f"(d[92]), "+f"(d[93]), "+f"(d[94]), "+f"(d[95]) :: "memory");
}

__device__ __forceinline__ void acc_fence(float (&d)[28]) {
  asm volatile("" : "+f"(d[0]), "+f"(d[1]), "+f"(d[2]), "+f"(d[3]), "+f"(d[4]), "+f"(d[5]), "+f"(d[6]), "+f"(d[7]), "+f"(d[8]), "+f"(d[9]), "+f"(d[10]), "+f"(d[11]), "+f"(d[12]), "+f"(d[13]), "+f"(d[14]), "+f"(d[15]), "+f"(d[16]), "+f"(d[17]), "+f"(d[18]), "+f"(d[19]), "+f"(d[20]), "+f"(d[21]), "+f"(d[22]), "+f"(d[23]), "+f"(d[24]), "+f"(d[25]), "+f"(d[26]), "+f"(d[27]) :: "memory");
}

__device__ __forceinline__ void acc_fence(float (&d)[48]) {
  asm volatile("" : "+f"(d[0]), "+f"(d[1]), "+f"(d[2]), "+f"(d[3]), "+f"(d[4]), "+f"(d[5]), "+f"(d[6]), "+f"(d[7]), "+f"(d[8]), "+f"(d[9]), "+f"(d[10]), "+f"(d[11]), "+f"(d[12]), "+f"(d[13]), "+f"(d[14]), "+f"(d[15]), "+f"(d[16]), "+f"(d[17]), "+f"(d[18]), "+f"(d[19]), "+f"(d[20]), "+f"(d[21]), "+f"(d[22]), "+f"(d[23]), "+f"(d[24]), "+f"(d[25]), "+f"(d[26]), "+f"(d[27]), "+f"(d[28]), "+f"(d[29]), "+f"(d[30]), "+f"(d[31]), "+f"(d[32]), "+f"(d[33]), "+f"(d[34]), "+f"(d[35]), "+f"(d[36]), "+f"(d[37]), "+f"(d[38]), "+f"(d[39]), "+f"(d[40]), "+f"(d[41]), "+f"(d[42]), "+f"(d[43]), "+f"(d[44]), "+f"(d[45]), "+f"(d[46]), "+f"(d[47]) :: "memory");
}

constexpr int FW_LD = 200;
__global__ void __launch_bounds__(384) fold_weights_kernel(const __nv_bfloat16* __restrict__ wqkv_t, const __nv_bfloat16* __restrict__ wo_t,
                                    const __nv_bfloat16* __restrict__ wqkv_s, const __nv_bfloat16* __restrict__ wo_s) {
  extern __shared__ __align__(16) uint8_t fsm[];
  __nv_bfloat16* As = reinterpret_cast<__nv_bfloat16*>(fsm);
  float* part = reinterpret_cast<float*>(fsm + CH * FW_LD * 2);
  float* part2 = part + 16 * CH;
  float* cm = part2 + 16 * CH;
  float* Bs = cm + CH;
  const int mat = blockIdx.y, n0 = blockIdx.x * 16, tid = threadIdx.x;
  const __nv_bfloat16* wqkv = (mat < 2) ? wqkv_t : wqkv_s;
  const __nv_bfloat16* wo = (mat < 2) ? wo_t : wo_s;
  const bool isM = (mat & 1) == 0;
  const int offA = isM ? 0 : 2 * CH;
  const int cg = tid % 24, rg = tid / 24;
  {
    uint4 va[12], vb[12];
#pragma unroll
    for (int i = 0; i < 12; i++) va[i] = *reinterpret_cast<const uint4*>(wqkv + (rg * 12 + i) * 3 * CH + offA + cg * 8);
    if (isM) {
#pragma unroll
      for (int i = 0; i < 12; i++) vb[i] = *reinterpret_cast<const uint4*>(wqkv + (rg * 12 + i) * 3 * CH + CH + cg * 8);
    } else {
#pragma unroll
      for (int i = 0; i < 12; i++) vb[i] = make_uint4(0, 0, 0, 0);
    }
    float sa[8] = {0.f, 0.f, 0.f, 0.f, 0.f, 0.f, 0.f, 0.f}, sb[8] = {0.f, 0.f, 0.f, 0.f, 0.f, 0.f, 0.f, 0.f};
#pragma unroll
    for (int i = 0; i < 12; i++) {
      *reinterpret_cast<uint4*>(As + (rg * 12 + i) * FW_LD + cg * 8) = va[i];
      sa[0] += bf_lo(va[i].x); sa[1] += bf_hi(va[i].x); sa[2] += bf_lo(va[i].y); sa[3] += bf_hi(va[i].y);
      sa[4] += bf_lo(va[i].z); sa[5] += bf_hi(va[i].z); sa[6] += bf_lo(va[i].w); sa[7] += bf_hi(va[i].w);
      sb[0] += bf_lo(vb[i].x); sb[1] += bf_hi(vb[i].x); sb[2] += bf_lo(vb[i].y); sb[3] += bf_hi(vb[i].y);
      sb[4] += bf_lo(vb[i].z); sb[5] += bf_hi(vb[i].z); sb[6] += bf_lo(vb[i].w); sb[7] += bf_hi(vb[i].w);
    }
#pragma unroll
    for (int e = 0; e < 8; e++) { part[rg * CH + cg * 8 + e] = sa[e]; part2[rg * CH + cg * 8 + e] = sb[e]; }
  }
  __syncthreads();
  if (tid < CH) {
    float s = 0.f, s2 = 0.f;
#pragma unroll
    for (int r = 0; r < 16; r++) { s += part[r * CH + tid]; s2 += part2[r * CH + tid]; }
    cm[tid] = s * (1.0f / CH);
    const float cmB = s2 * (1.0f / CH);
#pragma unroll
    for (int n = 0; n < 16; n++)
      Bs[n * 196 + tid] = isM ? (__bfloat162float(wqkv[(n0 + n) * 3 * CH + CH + tid]) - cmB) : __bfloat162float(wo[tid * CH + n0 + n]);
  }
  __syncthreads();
  const int k = tid >> 1, nh = (tid & 1) * 8;
  float acc[8];
#pragma unroll
  for (int n = 0; n < 8; n++) acc[n] = 0.f;
#pragma unroll 4
  for (int c = 0; c < CH; c += 4) {
    const uint2 u = *reinterpret_cast<const uint2*>(As + k * FW_LD + c);
    const float4 m4 = *reinterpret_cast<const float4*>(cm + c);
    const float a0 = bf_lo(u.x) - m4.x, a1 = bf_hi(u.x) - m4.y, a2 = bf_lo(u.y) - m4.z, a3 = bf_hi(u.y) - m4.w;
#pragma unroll
    for (int n = 0; n < 8; n++) {
      const float4 b = *reinterpret_cast<const float4*>(Bs + (nh + n) * 196 + c);
      acc[n] = fmaf(a0, b.x, acc[n]); acc[n] = fmaf(a1, b.y, acc[n]);
      acc[n] = fmaf(a2, b.z, acc[n]); acc[n] = fmaf(a3, b.w, acc[n]);
    }
  }
  const int p = k >> 6, kc = k & 63;
#pragma unroll
  for (int n = 0; n < 8; n++) {
    const int nn = n0 + nh + n;
    g_w[mat][p * (CH * 64) + nn * 64 + (((kc >> 3) ^ (nn & 7)) << 3) + (kc & 7)] = __float2bfloat16(acc[n]);
  }
}
constexpr int FW_SMEM = CH * FW_LD * 2 + (32 * CH + CH + 16 * 196) * 4;

struct Params {
  int role;
};

__device__ __forceinline__ uint32_t frag_addr(uint32_t slot_rowoff, uint32_t sw, int hiblk, int kk) {
  const int ci = 2 * kk + hiblk;
  return slot_rowoff + (ci >> 3) * PANEL_X + ((((uint32_t)ci & 7u) ^ sw) << 4);
}

__device__ __forceinline__ float row_rstd(uint32_t slot, int w, int lane) {
  const int row = 16 * w + (lane >> 1), half = lane & 1;
  const uint32_t rbase = slot + row * 128, sw = row & 7;
  float s0 = 0.f, s1 = 0.f, s2 = 0.f, s3 = 0.f, q0 = 0.f, q1 = 0.f, q2 = 0.f, q3 = 0.f;
#pragma unroll
  for (int i = 0; i < 12; i++) {
    const int c = half * 12 + i;
    const uint4 v = lds128(rbase + (c >> 3) * PANEL_X + ((((uint32_t)c & 7u) ^ sw) << 4));
    float lo, hi;
    lo = bf_lo(v.x); hi = bf_hi(v.x); s0 += lo; s1 += hi; q0 = fmaf(lo, lo, q0); q1 = fmaf(hi, hi, q1);
    lo = bf_lo(v.y); hi = bf_hi(v.y); s2 += lo; s3 += hi; q2 = fmaf(lo, lo, q2); q3 = fmaf(hi, hi, q3);
    lo = bf_lo(v.z); hi = bf_hi(v.z); s0 += lo; s1 += hi; q0 = fmaf(lo, lo, q0); q1 = fmaf(hi, hi, q1);
    lo = bf_lo(v.w); hi = bf_hi(v.w); s2 += lo; s3 += hi; q2 = fmaf(lo, lo, q2); q3 = fmaf(hi, hi, q3);
  }
  float s = (s0 + s1) + (s2 + s3), ss = (q0 + q1) + (q2 + q3);
  s += __shfl_xor_sync(0xffffffffu, s, 1);
  ss += __shfl_xor_sync(0xffffffffu, ss, 1);
  const float mean = s * (1.0f / CH);
  const float var = fmaxf(ss * (1.0f / CH) - mean * mean, 0.f);
  return rsqrtf(var + 1e-5f);
}

__global__ void __launch_bounds__(NWG * 128 + 128, 1)
swin_main_kernel(const __grid_constant__ CUtensorMap map_in, const __grid_constant__ CUtensorMap map_out, const int role) {
  extern __shared__ __align__(1024) uint8_t smem_raw[];
  const uint32_t sbase = smem_u32(smem_raw);
  const int tid = threadIdx.x, wg = tid >> 7, t128 = tid & 127, w = t128 >> 5, lane = tid & 31;
  const int g = lane >> 2, q = lane & 3;

  const uint32_t bar_w = sbase + SMEM_MISC;
  float* rbuf = reinterpret_cast<float*>(smem_raw + SMEM_RBUF) + wg * 64;

  if (tid == 0) {
    mbar_init(bar_w, 1);
    for (int i = 0; i < NSLOT; i++) { mbar_init(sbase + SMEM_MISC + 8 + 8 * i, 1); mbar_init(sbase + SMEM_MISC + 64 + 8 * i, 128); }
    asm volatile("fence.mbarrier_init.release.cluster;" ::: "memory");
  }
  for (int i = tid; i < NSLOT * SLOT_BYTES / 16; i += NWG * 128 + 128)
    *reinterpret_cast<uint4*>(smem_raw + SMEM_SLOT + i * 16) = make_uint4(0, 0, 0, 0);
  fence_proxy_async();
  __syncthreads();

  const int nunits = role == 0 ? NTILE_A : NUNIT_B;
  const int ustride = gridDim.x;
  const int nj = (nunits - (int)blockIdx.x + ustride - 1) / ustride;
  const uint32_t tx_bytes = role == 0 ? SLOT_BYTES : 3 * 49 * 128;

  auto coords = [&](int j, int& c1, int& c2, int& c3) {
    const int u = blockIdx.x + j * ustride;
    if (role == 0) { c1 = 0; c2 = (u % 14) * 16; c3 = u / 14; }
    else { const int t = u & 3, wx = (u >> 2) & 31, wy = u >> 7; c1 = wx * 7; c2 = wy * 7; c3 = t; }
  };
  auto issue_load = [&](int j) {
    int c1, c2, c3; coords(j, c1, c2, c3);
    const int sl = j % NSLOT;
    const uint32_t bar = sbase + SMEM_MISC + 8 + 8 * sl;
    mbar_expect_tx(bar, tx_bytes);
#pragma unroll
    for (int p = 0; p < 3; p++) tma_load_4d(sbase + SMEM_SLOT + sl * SLOT_BYTES + p * PANEL_X, &map_in, p * 64, c1, c2, c3, bar);
  };
  auto prefetch_l2 = [&](int j) {
    if (j < nj) {
      int c1, c2, c3; coords(j, c1, c2, c3);
#pragma unroll
      for (int p = 0; p < 3; p++) tma_prefetch_4d(&map_in, p * 64, c1, c2, c3);
    }
  };

  if (tid >= NWG * 128) {
    asm volatile("setmaxnreg.dec.sync.aligned.u32 40;");
    if (tid == NWG * 128) {
      mbar_expect_tx(bar_w, 2 * WMAT_BYTES);
      bulk_load(sbase + SMEM_W0, &g_w[role * 2][0], WMAT_BYTES, bar_w);
      bulk_load(sbase + SMEM_W1, &g_w[role * 2 + 1][0], WMAT_BYTES, bar_w);
      for (int j = 0; j < NSLOT && j < nj; j++) issue_load(j);
      prefetch_l2(NSLOT); prefetch_l2(NSLOT + 1);
      for (int j = 0; j < nj; j++) {
        const int sl = j % NSLOT;
        mbar_wait(sbase + SMEM_MISC + 64 + 8 * sl, (j / NSLOT) & 1);
        int c1, c2, c3; coords(j, c1, c2, c3);
#pragma unroll
        for (int p = 0; p < 3; p++) tma_store_4d(&map_out, sbase + SMEM_SLOT + sl * SLOT_BYTES + p * PANEL_X, p * 64, c1, c2, c3);
        bulk_commit();
        bulk_wait_read0();
        if (j + NSLOT < nj) issue_load(j + NSLOT);
        prefetch_l2(j + NSLOT + 2);
      }
      bulk_wait0();
    }
    return;
  }
  asm volatile("setmaxnreg.inc.sync.aligned.u32 232;");
  mbar_wait(bar_w, 0);

  const int blk = lane >> 3;
  const int frow = 16 * w + (lane & 7) + ((blk & 1) << 3);
  const uint32_t fsw = frow & 7;
  const int fhi = blk >> 1;

  const uint64_t dW0 = make_desc(sbase + SMEM_W0, 16, 1024);
  const uint64_t dW1 = make_desc(sbase + SMEM_W1, 16, 1024);

  const float scale_l2e = 0.07216878364870322f * 1.4426950408889634f;

  for (int j = wg; j < nj; j += NWG) {
    const int sl = j % NSLOT;
    const uint32_t slot = sbase + SMEM_SLOT + sl * SLOT_BYTES;
    const uint32_t frowoff = slot + frow * 128;
    const uint64_t dX = make_desc(slot, 16, 1024);
    const uint64_t dXmn = make_desc(slot, PANEL_X, 1024);
    PH(0);
    mbar_wait(sbase + SMEM_MISC + 8 + 8 * sl, (j / NSLOT) & 1);
    PH(1);

    float acc[96];
    wgmma_fence();
#pragma unroll
    for (int kk = 0; kk < 12; kk++) {
      const uint32_t off = (kk >> 2) * PANEL_X + (kk & 3) * 32;
      const uint32_t offw = (kk >> 2) * PANEL_W + (kk & 3) * 32;
      wgmma_n192_ss(acc, dX + (off >> 4), dW0 + (offw >> 4), kk);
    }
    wgmma_commit();
    PH(2);
    const float rmine = row_rstd(slot, w, lane);
    PH(3);
    uint32_t fr[48], xf[48];

    if (role == 0) {
      wgmma_wait0(); acc_fence(acc);
      PH(4);
#pragma unroll
      for (int i = 0; i < 48; i++) fr[i] = pack_bf16(acc[2 * i], acc[2 * i + 1]);
#pragma unroll
      for (int kk = 0; kk < 12; kk++) ldsm_x4(frag_addr(frowoff, fsw, fhi, kk), xf[4 * kk], xf[4 * kk + 1], xf[4 * kk + 2], xf[4 * kk + 3]);
      float d0[4] = {0.f, 0.f, 0.f, 0.f}, d1[4] = {0.f, 0.f, 0.f, 0.f};
      {
        float e0[4] = {0.f, 0.f, 0.f, 0.f}, e1[4] = {0.f, 0.f, 0.f, 0.f};
#pragma unroll
        for (int kk = 0; kk < 12; kk += 2) {
          mma_16816(d0[0], d0[1], d0[2], d0[3], fr[4 * kk], fr[4 * kk + 1], fr[4 * kk + 2], fr[4 * kk + 3], xf[4 * kk], xf[4 * kk + 2]);
          mma_16816(d1[0], d1[1], d1[2], d1[3], fr[4 * kk], fr[4 * kk + 1], fr[4 * kk + 2], fr[4 * kk + 3], xf[4 * kk + 1], xf[4 * kk + 3]);
          mma_16816(e0[0], e0[1], e0[2], e0[3], fr[4 * kk + 4], fr[4 * kk + 5], fr[4 * kk + 6], fr[4 * kk + 7], xf[4 * kk + 4], xf[4 * kk + 6]);
          mma_16816(e1[0], e1[1], e1[2], e1[3], fr[4 * kk + 4], fr[4 * kk + 5], fr[4 * kk + 6], fr[4 * kk + 7], xf[4 * kk + 5], xf[4 * kk + 7]);
        }
#pragma unroll
        for (int i = 0; i < 4; i++) { d0[i] += e0[i]; d1[i] += e1[i]; }
      }
      const float rA = __shfl_sync(0xffffffffu, rmine, 2 * g);
      const float rB = __shfl_sync(0xffffffffu, rmine, 2 * g + 16);
      const float k0 = __shfl_sync(0xffffffffu, rmine, 4 * q);
      const float k1 = __shfl_sync(0xffffffffu, rmine, 4 * q + 2);
      const float k2 = __shfl_sync(0xffffffffu, rmine, 4 * q + 16);
      const float k3 = __shfl_sync(0xffffffffu, rmine, 4 * q + 18);
      const bool valid = (g >> 2) == (q >> 1);
      float sa0 = d0[0] * k0 * (rA * scale_l2e), sa1 = d0[1] * k1 * (rA * scale_l2e);
      float sb0 = d1[2] * k2 * (rB * scale_l2e), sb1 = d1[3] * k3 * (rB * scale_l2e);
      float ma = fmaxf(sa0, sa1), mb = fmaxf(sb0, sb1);
      ma = fmaxf(ma, __shfl_xor_sync(0xffffffffu, ma, 1));
      mb = fmaxf(mb, __shfl_xor_sync(0xffffffffu, mb, 1));
      const float ea0 = exp2f(sa0 - ma), ea1 = exp2f(sa1 - ma);
      const float eb0 = exp2f(sb0 - mb), eb1 = exp2f(sb1 - mb);
      float suma = ea0 + ea1, sumb = eb0 + eb1;
      suma += __shfl_xor_sync(0xffffffffu, suma, 1);
      sumb += __shfl_xor_sync(0xffffffffu, sumb, 1);
      const float ia = __fdividef(1.f, suma), ib = __fdividef(1.f, sumb);
      const uint32_t pa0 = valid ? pack_bf16(ea0 * ia * k0, ea1 * ia * k1) : 0u;
      const uint32_t pa3 = valid ? pack_bf16(eb0 * ib * k2, eb1 * ib * k3) : 0u;
      PH(5);
#pragma unroll
      for (int hh = 0; hh < 2; hh++) {
        uint32_t bt[24];
#pragma unroll
        for (int jj = 0; jj < 6; jj++) ldsm_x4_t(frag_addr(frowoff, fsw, fhi, hh * 6 + jj), bt[4 * jj], bt[4 * jj + 1], bt[4 * jj + 2], bt[4 * jj + 3]);
#pragma unroll
        for (int jj = 0; jj < 6; jj++) {
          const int o = 8 * (hh * 6 + jj);
          acc[o + 0] = 0.f; acc[o + 1] = 0.f; acc[o + 2] = 0.f; acc[o + 3] = 0.f;
          acc[o + 4] = 0.f; acc[o + 5] = 0.f; acc[o + 6] = 0.f; acc[o + 7] = 0.f;
          mma_16816(acc[o + 0], acc[o + 1], acc[o + 2], acc[o + 3], pa0, 0u, 0u, pa3, bt[4 * jj], bt[4 * jj + 1]);
          mma_16816(acc[o + 4], acc[o + 5], acc[o + 6], acc[o + 7], pa0, 0u, 0u, pa3, bt[4 * jj + 2], bt[4 * jj + 3]);
        }
      }
    } else {
      if ((lane & 1) == 0) rbuf[16 * w + (lane >> 1)] = rmine;
      wg_bar(1 + wg);
      wgmma_wait0(); acc_fence(acc);
      PH(4);
#pragma unroll
      for (int i = 0; i < 48; i++) fr[i] = pack_bf16(acc[2 * i], acc[2 * i + 1]);
      float s[28];
      wgmma_fence();
#pragma unroll
      for (int kk = 0; kk < 12; kk++) {
        const uint32_t off = (kk >> 2) * PANEL_X + (kk & 3) * 32;
        wgmma_n56_rs(s, fr[4 * kk], fr[4 * kk + 1], fr[4 * kk + 2], fr[4 * kk + 3], dX + (off >> 4), kk);
      }
      wgmma_commit();
      float rj[14];
#pragma unroll
      for (int j = 0; j < 7; j++) {
        const float2 v = *reinterpret_cast<const float2*>(&rbuf[8 * j + 2 * q]);
        rj[2 * j] = v.x; rj[2 * j + 1] = v.y;
      }
      const float ri0 = rbuf[16 * w + g] * scale_l2e, ri1 = rbuf[16 * w + g + 8] * scale_l2e;
      wgmma_wait0(); acc_fence(s);
      PH(5);
      float m0 = -INFINITY, m1 = -INFINITY;
#pragma unroll
      for (int j = 0; j < 7; j++) {
#pragma unroll
        for (int e = 0; e < 2; e++) {
          const bool ok = (j < 6) || (2 * q + e == 0);
          float v0 = s[4 * j + e] * rj[2 * j + e] * ri0;
          float v1 = s[4 * j + 2 + e] * rj[2 * j + e] * ri1;
          v0 = ok ? v0 : -INFINITY; v1 = ok ? v1 : -INFINITY;
          s[4 * j + e] = v0; s[4 * j + 2 + e] = v1;
          m0 = fmaxf(m0, v0); m1 = fmaxf(m1, v1);
        }
      }
      m0 = fmaxf(m0, __shfl_xor_sync(0xffffffffu, m0, 1)); m0 = fmaxf(m0, __shfl_xor_sync(0xffffffffu, m0, 2));
      m1 = fmaxf(m1, __shfl_xor_sync(0xffffffffu, m1, 1)); m1 = fmaxf(m1, __shfl_xor_sync(0xffffffffu, m1, 2));
      float sum0 = 0.f, sum1 = 0.f;
#pragma unroll
      for (int j = 0; j < 7; j++) {
#pragma unroll
        for (int e = 0; e < 2; e++) {
          const float e0 = exp2f(s[4 * j + e] - m0), e1 = exp2f(s[4 * j + 2 + e] - m1);
          s[4 * j + e] = e0; s[4 * j + 2 + e] = e1;
          sum0 += e0; sum1 += e1;
        }
      }
      sum0 += __shfl_xor_sync(0xffffffffu, sum0, 1); sum0 += __shfl_xor_sync(0xffffffffu, sum0, 2);
      sum1 += __shfl_xor_sync(0xffffffffu, sum1, 1); sum1 += __shfl_xor_sync(0xffffffffu, sum1, 2);
      const float i0 = __fdividef(1.f, sum0), i1 = __fdividef(1.f, sum1);
      uint32_t pa[16];
#pragma unroll
      for (int j = 0; j < 7; j++) {
        pa[(j >> 1) * 4 + (j & 1) * 2 + 0] = pack_bf16(s[4 * j] * i0 * rj[2 * j], s[4 * j + 1] * i0 * rj[2 * j + 1]);
        pa[(j >> 1) * 4 + (j & 1) * 2 + 1] = pack_bf16(s[4 * j + 2] * i1 * rj[2 * j], s[4 * j + 3] * i1 * rj[2 * j + 1]);
      }
      pa[14] = 0u; pa[15] = 0u;
      PH(6);
      wgmma_fence();
#pragma unroll
      for (int kk = 0; kk < 4; kk++)
        wgmma_n192_rs_tb(acc, pa[4 * kk], pa[4 * kk + 1], pa[4 * kk + 2], pa[4 * kk + 3], dXmn + ((kk * 2048) >> 4), kk);
      wgmma_commit();
      wgmma_wait0(); acc_fence(acc);
    }

    PH(7);
#pragma unroll
    for (int i = 0; i < 48; i++) fr[i] = pack_bf16(acc[2 * i], acc[2 * i + 1]);
    wgmma_fence();
#pragma unroll
    for (int kk = 0; kk < 12; kk++) {
      const uint32_t offw = (kk >> 2) * PANEL_W + (kk & 3) * 32;
      wgmma_n192_rs(acc, fr[4 * kk], fr[4 * kk + 1], fr[4 * kk + 2], fr[4 * kk + 3], dW1 + (offw >> 4), kk);
    }
    wgmma_commit();
    if (role != 0) {
#pragma unroll
      for (int kk = 0; kk < 12; kk++) ldsm_x4(frag_addr(frowoff, fsw, fhi, kk), xf[4 * kk], xf[4 * kk + 1], xf[4 * kk + 2], xf[4 * kk + 3]);
    }
    wgmma_wait0(); acc_fence(acc);
    PH(8);
    wg_bar(1 + wg);
    PH(9);
#pragma unroll
    for (int kk = 0; kk < 12; kk++) {
      const uint32_t o0 = add_bf16x2(xf[4 * kk + 0], pack_bf16(acc[8 * kk + 0], acc[8 * kk + 1]));
      const uint32_t o1 = add_bf16x2(xf[4 * kk + 1], pack_bf16(acc[8 * kk + 2], acc[8 * kk + 3]));
      const uint32_t o2 = add_bf16x2(xf[4 * kk + 2], pack_bf16(acc[8 * kk + 4], acc[8 * kk + 5]));
      const uint32_t o3 = add_bf16x2(xf[4 * kk + 3], pack_bf16(acc[8 * kk + 6], acc[8 * kk + 7]));
      stsm_x4(frag_addr(frowoff, fsw, fhi, kk), o0, o1, o2, o3);
    }
    PH(10);
    fence_proxy_async();
    mbar_arrive(sbase + SMEM_MISC + 64 + 8 * sl);
    PH(11);
  }
}

typedef CUresult (*EncodeTiledFn)(CUtensorMap*, CUtensorMapDataType, cuuint32_t, void*, const cuuint64_t*, const cuuint64_t*,
                                  const cuuint32_t*, const cuuint32_t*, CUtensorMapInterleave, CUtensorMapSwizzle,
                                  CUtensorMapL2promotion, CUtensorMapFloatOOBfill);

bool make_map(EncodeTiledFn fn, CUtensorMap* m, void* base, bool pixel_major) {
  cuuint64_t dims[4]; cuuint64_t strides[3]; cuuint32_t box[4]; cuuint32_t es[4] = {1, 1, 1, 1};
  const cuuint64_t sC = (cuuint64_t)CH * 2, sW = sC * WW, sT = sW * HH;
  if (pixel_major) {
    dims[0] = CH; dims[1] = TT; dims[2] = WW; dims[3] = HH;
    strides[0] = sT; strides[1] = sC; strides[2] = sW;
    box[0] = 64; box[1] = 4; box[2] = 16; box[3] = 1;
  } else {
    dims[0] = CH; dims[1] = WW; dims[2] = HH; dims[3] = TT;
    strides[0] = sC; strides[1] = sW; strides[2] = sT;
    box[0] = 64; box[1] = 7; box[2] = 7; box[3] = 1;
  }
  return fn(m, CU_TENSOR_MAP_DATA_TYPE_BFLOAT16, 4, base, dims, strides, box, es, CU_TENSOR_MAP_INTERLEAVE_NONE,
            CU_TENSOR_MAP_SWIZZLE_128B, CU_TENSOR_MAP_L2_PROMOTION_L2_256B, CU_TENSOR_MAP_FLOAT_OOB_FILL_NONE) == CUDA_SUCCESS;
}

}

extern "C" void kernel_launch(void* const* d_in, const int* in_sizes, int n_in, void* d_out, int out_size) {
  const __nv_bfloat16* x = (const __nv_bfloat16*)d_in[0];
  const __nv_bfloat16* wqkv_t = (const __nv_bfloat16*)d_in[1];
  const __nv_bfloat16* wo_t = (const __nv_bfloat16*)d_in[2];
  const __nv_bfloat16* wqkv_s = (const __nv_bfloat16*)d_in[3];
  const __nv_bfloat16* wo_s = (const __nv_bfloat16*)d_in[4];

  static bool init = false;
  static CUtensorMap mA_in, mA_out, mB_in, mB_out;
  static void* last_x = nullptr; static void* last_out = nullptr;
  static int nsm = 132;
  if (!init || last_x != d_in[0] || last_out != d_out) {
    void* fnp = nullptr; cudaDriverEntryPointQueryResult qr;
    cudaGetDriverEntryPoint("cuTensorMapEncodeTiled", &fnp, cudaEnableDefault, &qr);
    EncodeTiledFn fn = (EncodeTiledFn)fnp;
    void* x1p = nullptr; cudaGetSymbolAddress(&x1p, g_x1);
    make_map(fn, &mA_in, (void*)x, true);
    make_map(fn, &mA_out, x1p, true);
    make_map(fn, &mB_in, x1p, false);
    make_map(fn, &mB_out, d_out, false);
    cudaFuncSetAttribute(fold_weights_kernel, cudaFuncAttributeMaxDynamicSharedMemorySize, FW_SMEM);
    cudaFuncSetAttribute(swin_main_kernel, cudaFuncAttributeMaxDynamicSharedMemorySize, SMEM_TOTAL);
    cudaDeviceGetAttribute(&nsm, cudaDevAttrMultiProcessorCount, 0);
    init = true; last_x = d_in[0]; last_out = d_out;
  }
  fold_weights_kernel<<<dim3(12, 4), 384, FW_SMEM>>>(wqkv_t, wo_t, wqkv_s, wo_s);
  swin_main_kernel<<<nsm, NWG * 128 + 128, SMEM_TOTAL>>>(mA_in, mA_out, 0);
  swin_main_kernel<<<nsm, NWG * 128 + 128, SMEM_TOTAL>>>(mB_in, mB_out, 1);
}
```

```cpp
#include <cuda_runtime.h>
#include <cuda_bf16.h>
#include <cuda.h>
#include <stdint.h>

namespace {

constexpr int CH = 192;
constexpr int TT = 4, HH = 224, WW = 224;
constexpr int NTOK = TT * HH * WW;
constexpr int PANEL_X = 64 * 128;
constexpr int SLOT_BYTES = 3 * PANEL_X;
constexpr int PANEL_W = 192 * 128;
constexpr int WMAT_BYTES = 3 * PANEL_W;
constexpr int NWG = 2;
constexpr int NSLOT = 3;
constexpr int SMEM_W0 = 0;
constexpr int SMEM_W1 = WMAT_BYTES;
constexpr int SMEM_SLOT = 2 * WMAT_BYTES;
constexpr int SMEM_MISC = SMEM_SLOT + NSLOT * SLOT_BYTES;
constexpr int SMEM_RBUF = SMEM_MISC + 128;
constexpr int SMEM_TOTAL = SMEM_RBUF + NWG * 64 * 4;

constexpr int NTILE_A = HH * (WW / 16);
constexpr int NUNIT_B = 32 * 32 * 4;
#define NUM_A 56

__device__ __nv_bfloat16 g_x1[(size_t)NTOK * CH];
__device__ unsigned int g_band_cnt[32];
__device__ __align__(1024) __nv_bfloat16 g_w[4][CH * CH];

#define PH(i) do {} while (0)
__device__ __forceinline__ uint32_t smem_u32(const void* p) { return (uint32_t)__cvta_generic_to_shared(p); }

__device__ __forceinline__ void mbar_init(uint32_t bar, uint32_t count) {
  asm volatile("mbarrier.init.shared::cta.b64 [%0], %1;" :: "r"(bar), "r"(count));
}
__device__ __forceinline__ void mbar_expect_tx(uint32_t bar, uint32_t bytes) {
  asm volatile("mbarrier.arrive.expect_tx.shared::cta.b64 _, [%0], %1;" :: "r"(bar), "r"(bytes) : "memory");
}
__device__ __forceinline__ void mbar_arrive(uint32_t bar) {
  asm volatile("mbarrier.arrive.shared::cta.b64 _, [%0];" :: "r"(bar) : "memory");
}
__device__ __forceinline__ void mbar_wait(uint32_t bar, uint32_t parity) {
  asm volatile(
    "{\n.reg .pred p;\n"
    "WAIT_%=:\n"
    "mbarrier.try_wait.parity.shared::cta.b64 p, [%0], %1;\n"
    "@p bra DONE_%=;\n"
    "bra WAIT_%=;\n"
    "DONE_%=:\n}\n" :: "r"(bar), "r"(parity) : "memory");
}
__device__ __forceinline__ void tma_load_4d(uint32_t dst, const CUtensorMap* map, int c0, int c1, int c2, int c3, uint32_t bar) {
  asm volatile("cp.async.bulk.tensor.4d.shared::cluster.global.tile.mbarrier::complete_tx::bytes [%0], [%1, {%2, %3, %4, %5}], [%6];"
    :: "r"(dst), "l"(map), "r"(c0), "r"(c1), "r"(c2), "r"(c3), "r"(bar) : "memory");
}
__device__ __forceinline__ void tma_prefetch_4d(const CUtensorMap* map, int c0, int c1, int c2, int c3) {
  asm volatile("cp.async.bulk.prefetch.tensor.4d.L2.global.tile [%0, {%1, %2, %3, %4}];"
    :: "l"(map), "r"(c0), "r"(c1), "r"(c2), "r"(c3) : "memory");
}
__device__ __forceinline__ void tma_store_4d(const CUtensorMap* map, uint32_t src, int c0, int c1, int c2, int c3) {
  asm volatile("cp.async.bulk.tensor.4d.global.shared::cta.tile.bulk_group [%0, {%1, %2, %3, %4}], [%5];"
    :: "l"(map), "r"(c0), "r"(c1), "r"(c2), "r"(c3), "r"(src) : "memory");
}
__device__ __forceinline__ void bulk_load(uint32_t dst, const void* src, uint32_t bytes, uint32_t bar) {
  asm volatile("cp.async.bulk.shared::cluster.global.mbarrier::complete_tx::bytes [%0], [%1], %2, [%3];"
    :: "r"(dst), "l"(src), "r"(bytes), "r"(bar) : "memory");
}
__device__ __forceinline__ void bulk_commit() { asm volatile("cp.async.bulk.commit_group;" ::: "memory"); }
__device__ __forceinline__ void bulk_wait_read0() { asm volatile("cp.async.bulk.wait_group.read 0;" ::: "memory"); }
__device__ __forceinline__ void bulk_wait0() { asm volatile("cp.async.bulk.wait_group 0;" ::: "memory"); }
__device__ __forceinline__ void fence_proxy_async() { asm volatile("fence.proxy.async.shared::cta;" ::: "memory"); }
__device__ __forceinline__ void wg_bar(int id) { asm volatile("bar.sync %0, 128;" :: "r"(id) : "memory"); }
__device__ __forceinline__ void wgmma_fence() { asm volatile("wgmma.fence.sync.aligned;" ::: "memory"); }
__device__ __forceinline__ void wgmma_commit() { asm volatile("wgmma.commit_group.sync.aligned;" ::: "memory"); }
__device__ __forceinline__ void wgmma_wait0() { asm volatile("wgmma.wait_group.sync.aligned 0;" ::: "memory"); }

__device__ __forceinline__ uint64_t make_desc(uint32_t saddr, uint32_t lbo, uint32_t sbo) {
  return (uint64_t)((saddr & 0x3FFFF) >> 4) | ((uint64_t)((lbo & 0x3FFFF) >> 4) << 16) |
         ((uint64_t)((sbo & 0x3FFFF) >> 4) << 32) | ((uint64_t)1 << 62);
}
__device__ __forceinline__ uint32_t pack_bf16(float lo, float hi) {
  uint32_t r; asm("cvt.rn.bf16x2.f32 %0, %1, %2;" : "=r"(r) : "f"(hi), "f"(lo)); return r;
}
__device__ __forceinline__ uint32_t add_bf16x2(uint32_t a, uint32_t b) {
  uint32_t r; asm("add.rn.bf16x2 %0, %1, %2;" : "=r"(r) : "r"(a), "r"(b)); return r;
}
__device__ __forceinline__ float bf_lo(uint32_t u) { return __uint_as_float(u << 16); }
__device__ __forceinline__ float bf_hi(uint32_t u) { return __uint_as_float(u & 0xffff0000u); }
__device__ __forceinline__ void ldsm_x4(uint32_t addr, uint32_t& r0, uint32_t& r1, uint32_t& r2, uint32_t& r3) {
  asm volatile("ldmatrix.sync.aligned.m8n8.x4.shared.b16 {%0,%1,%2,%3}, [%4];"
    : "=r"(r0), "=r"(r1), "=r"(r2), "=r"(r3) : "r"(addr) : "memory");
}
__device__ __forceinline__ void ldsm_x4_t(uint32_t addr, uint32_t& r0, uint32_t& r1, uint32_t& r2, uint32_t& r3) {
  asm volatile("ldmatrix.sync.aligned.m8n8.x4.trans.shared.b16 {%0,%1,%2,%3}, [%4];"
    : "=r"(r0), "=r"(r1), "=r"(r2), "=r"(r3) : "r"(addr) : "memory");
}
__device__ __forceinline__ void stsm_x4(uint32_t addr, uint32_t r0, uint32_t r1, uint32_t r2, uint32_t r3) {
  asm volatile("stmatrix.sync.aligned.m8n8.x4.shared.b16 [%0], {%1,%2,%3,%4};"
    :: "r"(addr), "r"(r0), "r"(r1), "r"(r2), "r"(r3) : "memory");
}
__device__ __forceinline__ void mma_16816(float& d0, float& d1, float& d2, float& d3,
                                          uint32_t a0, uint32_t a1, uint32_t a2, uint32_t a3, uint32_t b0, uint32_t b1) {
  asm volatile("mma.sync.aligned.m16n8k16.row.col.f32.bf16.bf16.f32 {%0,%1,%2,%3}, {%4,%5,%6,%7}, {%8,%9}, {%0,%1,%2,%3};"
    : "+f"(d0), "+f"(d1), "+f"(d2), "+f"(d3) : "r"(a0), "r"(a1), "r"(a2), "r"(a3), "r"(b0), "r"(b1));
}
__device__ __forceinline__ uint4 lds128(uint32_t addr) {
  uint4 v; asm volatile("ld.shared.v4.u32 {%0,%1,%2,%3}, [%4];" : "=r"(v.x), "=r"(v.y), "=r"(v.z), "=r"(v.w) : "r"(addr) : "memory");
  return v;
}

__device__ __forceinline__ void wgmma_n192_ss(float (&d)[96], uint64_t da, uint64_t db, int scale_d) {
  asm volatile("{\n.reg .pred p;\nsetp.ne.b32 p, %98, 0;\n"
    "wgmma.mma_async.sync.aligned.m64n192k16.f32.bf16.bf16 {%0, %1, %2, %3, %4, %5, %6, %7, %8, %9, %10, %11, %12, %13, %14, %15, %16, %17, %18, %19, %20, %21, %22, %23, %24, %25, %26, %27, %28, %29, %30, %31, %32, %33, %34, %35, %36, %37, %38, %39, %40, %41, %42, %43, %44, %45, %46, %47, %48, %49, %50, %51, %52, %53, %54, %55, %56, %57, %58, %59, %60, %61, %62, %63, %64, %65, %66, %67, %68, %69, %70, %71, %72, %73, %74, %75, %76, %77, %78, %79, %80, %81, %82, %83, %84, %85, %86, %87, %88, %89, %90, %91, %92, %93, %94, %95}, %96, %97, p, 1, 1, 0, 0;\n}\n"
    : "+f"(d[0]), "+f"(d[1]), "+f"(d[2]), "+f"(d[3]), "+f"(d[4]), "+f"(d[5]), "+f"(d[6]), "+f"(d[7]), "+f"(d[8]), "+f"(d[9]), "+f"(d[10]), "+f"(d[11]), "+f"(d[12]), "+f"(d[13]), "+f"(d[14]), "+f"(d[15]), "+f"(d[16]), "+f"(d[17]), "+f"(d[18]), "+f"(d[19]), "+f"(d[20]), "+f"(d[21]), "+f"(d[22]), "+f"(d[23]), "+f"(d[24]), "+f"(d[25]), "+f"(d[26]), "+f"(d[27]), "+f"(d[28]), "+f"(d[29]), "+f"(d[30]), "+f"(d[31]), "+f"(d[32]), "+f"(d[33]), "+f"(d[34]), "+f"(d[35]), "+f"(d[36]), "+f"(d[37]), "+f"(d[38]), "+f"(d[39]), "+f"(d[40]), "+f"(d[41]), "+f"(d[42]), "+f"(d[43]), "+f"(d[44]), "+f"(d[45]), "+f"(d[46]), "+f"(d[47]), "+f"(d[48]), "+f"(d[49]), "+f"(d[50]), "+f"(d[51]), "+f"(d[52]), "+f"(d[53]), "+f"(d[54]), "+f"(d[55]), "+f"(d[56]), "+f"(d[57]), "+f"(d[58]), "+f"(d[59]), "+f"(d[60]), "+f"(d[61]), "+f"(d[62]), "+f"(d[63]), "+f"(d[64]), "+f"(d[65]), "+f"(d[66]), "+f"(d[67]), "+f"(d[68]), "+f"(d[69]), "+f"(d[70]), "+f"(d[71]), "+f"(d[72]), "+f"(d[73]), "+f"(d[74]), "+f"(d[75]), "+f"(d[76]), "+f"(d[77]), "+f"(d[78]), "+f"(d[79]), "+f"(d[80]), "+f"(d[81]), "+f"(d[82]), "+f"(d[83]), "+f"(d[84]), "+f"(d[85]), "+f"(d[86]), "+f"(d[87]), "+f"(d[88]), "+f"(d[89]), "+f"(d[90]), "+f"(d[91]), "+f"(d[92]), "+f"(d[93]), "+f"(d[94]), "+f"(d[95])
    : "l"(da), "l"(db), "r"(scale_d));
}

__device__ __forceinline__ void wgmma_n192_rs(float (&d)[96], uint32_t a0, uint32_t a1, uint32_t a2, uint32_t a3, uint64_t db, int scale_d) {
  asm volatile("{\n.reg .pred p;\nsetp.ne.b32 p, %101, 0;\n"
    "wgmma.mma_async.sync.aligned.m64n192k16.f32.bf16.bf16 {%0, %1, %2, %3, %4, %5, %6, %7, %8, %9, %10, %11, %12, %13, %14, %15, %16, %17, %18, %19, %20, %21, %22, %23, %24, %25, %26, %27, %28, %29, %30, %31, %32, %33, %34, %35, %36, %37, %38, %39, %40, %41, %42, %43, %44, %45, %46, %47, %48, %49, %50, %51, %52, %53, %54, %55, %56, %57, %58, %59, %60, %61, %62, %63, %64, %65, %66, %67, %68, %69, %70, %71, %72, %73, %74, %75, %76, %77, %78, %79, %80, %81, %82, %83, %84, %85, %86, %87, %88, %89, %90, %91, %92, %93, %94, %95}, {%96, %97, %98, %99}, %100, p, 1, 1, 0;\n}\n"
    : "+f"(d[0]), "+f"(d[1]), "+f"(d[2]), "+f"(d[3]), "+f"(d[4]), "+f"(d[5]), "+f"(d[6]), "+f"(d[7]), "+f"(d[8]), "+f"(d[9]), "+f"(d[10]), "+f"(d[11]), "+f"(d[12]), "+f"(d[13]), "+f"(d[14]), "+f"(d[15]), "+f"(d[16]), "+f"(d[17]), "+f"(d[18]), "+f"(d[19]), "+f"(d[20]), "+f"(d[21]), "+f"(d[22]), "+f"(d[23]), "+f"(d[24]), "+f"(d[25]), "+f"(d[26]), "+f"(d[27]), "+f"(d[28]), "+f"(d[29]), "+f"(d[30]), "+f"(d[31]), "+f"(d[32]), "+f"(d[33]), "+f"(d[34]), "+f"(d[35]), "+f"(d[36]), "+f"(d[37]), "+f"(d[38]), "+f"(d[39]), "+f"(d[40]), "+f"(d[41]), "+f"(d[42]), "+f"(d[43]), "+f"(d[44]), "+f"(d[45]), "+f"(d[46]), "+f"(d[47]), "+f"(d[48]), "+f"(d[49]), "+f"(d[50]), "+f"(d[51]), "+f"(d[52]), "+f"(d[53]), "+f"(d[54]), "+f"(d[55]), "+f"(d[56]), "+f"(d[57]), "+f"(d[58]), "+f"(d[59]), "+f"(d[60]), "+f"(d[61]), "+f"(d[62]), "+f"(d[63]), "+f"(d[64]), "+f"(d[65]), "+f"(d[66]), "+f"(d[67]), "+f"(d[68]), "+f"(d[69]), "+f"(d[70]), "+f"(d[71]), "+f"(d[72]), "+f"(d[73]), "+f"(d[74]), "+f"(d[75]), "+f"(d[76]), "+f"(d[77]), "+f"(d[78]), "+f"(d[79]), "+f"(d[80]), "+f"(d[81]), "+f"(d[82]), "+f"(d[83]), "+f"(d[84]), "+f"(d[85]), "+f"(d[86]), "+f"(d[87]), "+f"(d[88]), "+f"(d[89]), "+f"(d[90]), "+f"(d[91]), "+f"(d[92]), "+f"(d[93]), "+f"(d[94]), "+f"(d[95])
    : "r"(a0), "r"(a1), "r"(a2), "r"(a3), "l"(db), "r"(scale_d));
}

__device__ __forceinline__ void wgmma_n192_rs_tb(float (&d)[96], uint32_t a0, uint32_t a1, uint32_t a2, uint32_t a3, uint64_t db, int scale_d) {
  asm volatile("{\n.reg .pred p;\nsetp.ne.b32 p, %101, 0;\n"
    "wgmma.mma_async.sync.aligned.m64n192k16.f32.bf16.bf16 {%0, %1, %2, %3, %4, %5, %6, %7, %8, %9, %10, %11, %12, %13, %14, %15, %16, %17, %18, %19, %20, %21, %22, %23, %24, %25, %26, %27, %28, %29, %30, %31, %32, %33, %34, %35, %36, %37, %38, %39, %40, %41, %42, %43, %44, %45, %46, %47, %48, %49, %50, %51, %52, %53, %54, %55, %56, %57, %58, %59, %60, %61, %62, %63, %64, %65, %66, %67, %68, %69, %70, %71, %72, %73, %74, %75, %76, %77, %78, %79, %80, %81, %82, %83, %84, %85, %86, %87, %88, %89, %90, %91, %92, %93, %94, %95}, {%96, %97, %98, %99}, %100, p, 1, 1, 1;\n}\n"
    : "+f"(d[0]), "+f"(d[1]), "+f"(d[2]), "+f"(d[3]), "+f"(d[4]), "+f"(d[5]), "+f"(d[6]), "+f"(d[7]), "+f"(d[8]), "+f"(d[9]), "+f"(d[10]), "+f"(d[11]), "+f"(d[12]), "+f"(d[13]), "+f"(d[14]), "+f"(d[15]), "+f"(d[16]), "+f"(d[17]), "+f"(d[18]), "+f"(d[19]), "+f"(d[20]), "+f"(d[21]), "+f"(d[22]), "+f"(d[23]), "+f"(d[24]), "+f"(d[25]), "+f"(d[26]), "+f"(d[27]), "+f"(d[28]), "+f"(d[29]), "+f"(d[30]), "+f"(d[31]), "+f"(d[32]), "+f"(d[33]), "+f"(d[34]), "+f"(d[35]), "+f"(d[36]), "+f"(d[37]), "+f"(d[38]), "+f"(d[39]), "+f"(d[40]), "+f"(d[41]), "+f"(d[42]), "+f"(d[43]), "+f"(d[44]), "+f"(d[45]), "+f"(d[46]), "+f"(d[47]), "+f"(d[48]), "+f"(d[49]), "+f"(d[50]), "+f"(d[51]), "+f"(d[52]), "+f"(d[53]), "+f"(d[54]), "+f"(d[55]), "+f"(d[56]), "+f"(d[57]), "+f"(d[58]), "+f"(d[59]), "+f"(d[60]), "+f"(d[61]), "+f"(d[62]), "+f"(d[63]), "+f"(d[64]), "+f"(d[65]), "+f"(d[66]), "+f"(d[67]), "+f"(d[68]), "+f"(d[69]), "+f"(d[70]), "+f"(d[71]), "+f"(d[72]), "+f"(d[73]), "+f"(d[74]), "+f"(d[75]), "+f"(d[76]), "+f"(d[77]), "+f"(d[78]), "+f"(d[79]), "+f"(d[80]), "+f"(d[81]), "+f"(d[82]), "+f"(d[83]), "+f"(d[84]), "+f"(d[85]), "+f"(d[86]), "+f"(d[87]), "+f"(d[88]), "+f"(d[89]), "+f"(d[90]), "+f"(d[91]), "+f"(d[92]), "+f"(d[93]), "+f"(d[94]), "+f"(d[95])
    : "r"(a0), "r"(a1), "r"(a2), "r"(a3), "l"(db), "r"(scale_d));
}

__device__ __forceinline__ void wgmma_n56_rs(float (&d)[28], uint32_t a0, uint32_t a1, uint32_t a2, uint32_t a3, uint64_t db, int scale_d) {
  asm volatile("{\n.reg .pred p;\nsetp.ne.b32 p, %33, 0;\n"
    "wgmma.mma_async.sync.aligned.m64n56k16.f32.bf16.bf16 {%0, %1, %2, %3, %4, %5, %6, %7, %8, %9, %10, %11, %12, %13, %14, %15, %16, %17, %18, %19, %20, %21, %22, %23, %24, %25, %26, %27}, {%28, %29, %30, %31}, %32, p, 1, 1, 0;\n}\n"
    : "+f"(d[0]), "+f"(d[1]), "+f"(d[2]), "+f"(d[3]), "+f"(d[4]), "+f"(d[5]), "+f"(d[6]), "+f"(d[7]), "+f"(d[8]), "+f"(d[9]), "+f"(d[10]), "+f"(d[11]), "+f"(d[12]), "+f"(d[13]), "+f"(d[14]), "+f"(d[15]), "+f"(d[16]), "+f"(d[17]), "+f"(d[18]), "+f"(d[19]), "+f"(d[20]), "+f"(d[21]), "+f"(d[22]), "+f"(d[23]), "+f"(d[24]), "+f"(d[25]), "+f"(d[26]), "+f"(d[27])
    : "r"(a0), "r"(a1), "r"(a2), "r"(a3), "l"(db), "r"(scale_d));
}

__device__ __forceinline__ void wgmma_n96_rs(float (&d)[48], uint32_t a0, uint32_t a1, uint32_t a2, uint32_t a3, uint64_t db, int scale_d) {
  asm volatile("{\n.reg .pred p;\nsetp.ne.b32 p, %53, 0;\n"
    "wgmma.mma_async.sync.aligned.m64n96k16.f32.bf16.bf16 {%0, %1, %2, %3, %4, %5, %6, %7, %8, %9, %10, %11, %12, %13, %14, %15, %16, %17, %18, %19, %20, %21, %22, %23, %24, %25, %26, %27, %28, %29, %30, %31, %32, %33, %34, %35, %36, %37, %38, %39, %40, %41, %42, %43, %44, %45, %46, %47}, {%48, %49, %50, %51}, %52, p, 1, 1, 0;\n}\n"
    : "+f"(d[0]), "+f"(d[1]), "+f"(d[2]), "+f"(d[3]), "+f"(d[4]), "+f"(d[5]), "+f"(d[6]), "+f"(d[7]), "+f"(d[8]), "+f"(d[9]), "+f"(d[10]), "+f"(d[11]), "+f"(d[12]), "+f"(d[13]), "+f"(d[14]), "+f"(d[15]), "+f"(d[16]), "+f"(d[17]), "+f"(d[18]), "+f"(d[19]), "+f"(d[20]), "+f"(d[21]), "+f"(d[22]), "+f"(d[23]), "+f"(d[24]), "+f"(d[25]), "+f"(d[26]), "+f"(d[27]), "+f"(d[28]), "+f"(d[29]), "+f"(d[30]), "+f"(d[31]), "+f"(d[32]), "+f"(d[33]), "+f"(d[34]), "+f"(d[35]), "+f"(d[36]), "+f"(d[37]), "+f"(d[38]), "+f"(d[39]), "+f"(d[40]), "+f"(d[41]), "+f"(d[42]), "+f"(d[43]), "+f"(d[44]), "+f"(d[45]), "+f"(d[46]), "+f"(d[47])
    : "r"(a0), "r"(a1), "r"(a2), "r"(a3), "l"(db), "r"(scale_d));
}

__device__ __forceinline__ void acc_fence(float (&d)[96]) {
  asm volatile("" : "+f"(d[0]), "+f"(d[1]), "+f"(d[2]), "+f"(d[3]), "+f"(d[4]), "+f"(d[5]), "+f"(d[6]), "+f"(d[7]), "+f"(d[8]), "+f"(d[9]), "+f"(d[10]), "+f"(d[11]), "+f"(d[12]), "+f"(d[13]), "+f"(d[14]), "+f"(d[15]), "+f"(d[16]), "+f"(d[17]), "+f"(d[18]), "+f"(d[19]), "+f"(d[20]), "+f"(d[21]), "+f"(d[22]), "+f"(d[23]), "+f"(d[24]), "+f"(d[25]), "+f"(d[26]), "+f"(d[27]), "+f"(d[28]), "+f"(d[29]), "+f"(d[30]), "+f"(d[31]), "+f"(d[32]), "+f"(d[33]), "+f"(d[34]), "+f"(d[35]), "+f"(d[36]), "+f"(d[37]), "+f"(d[38]), "+f"(d[39]), "+f"(d[40]), "+f"(d[41]), "+f"(d[42]), "+f"(d[43]), "+f"(d[44]), "+f"(d[45]), "+f"(d[46]), "+f"(d[47]), "+f"(d[48]), "+f"(d[49]), "+f"(d[50]), "+f"(d[51]), "+f"(d[52]), "+f"(d[53]), "+f"(d[54]), "+f"(d[55]), "+f"(d[56]), "+f"(d[57]), "+f"(d[58]), "+f"(d[59]), "+f"(d[60]), "+f"(d[61]), "+f"(d[62]), "+f"(d[63]), "+f"(d[64]), "+f"(d[65]), "+f"(d[66]), "+f"(d[67]), "+f"(d[68]), "+f"(d[69]), "+f"(d[70]), "+f"(d[71]), "+f"(d[72]), "+f"(d[73]), "+f"(d[74]), "+f"(d[75]), "+f"(d[76]), "+f"(d[77]), "+f"(d[78]), "+f"(d[79]), "+f"(d[80]), "+f"(d[81]), "+f"(d[82]), "+f"(d[83]), "+f"(d[84]), "+f"(d[85]), "+f"(d[86]), "+f"(d[87]), "+f"(d[88]), "+f"(d[89]), "+f"(d[90]), "+f"(d[91]), "+f"(d[92]), "+f"(d[93]), "+f"(d[94]), "+f"(d[95]) :: "memory");
}

__device__ __forceinline__ void acc_fence(float (&d)[28]) {
  asm volatile("" : "+f"(d[0]), "+f"(d[1]), "+f"(d[2]), "+f"(d[3]), "+f"(d[4]), "+f"(d[5]), "+f"(d[6]), "+f"(d[7]), "+f"(d[8]), "+f"(d[9]), "+f"(d[10]), "+f"(d[11]), "+f"(d[12]), "+f"(d[13]), "+f"(d[14]), "+f"(d[15]), "+f"(d[16]), "+f"(d[17]), "+f"(d[18]), "+f"(d[19]), "+f"(d[20]), "+f"(d[21]), "+f"(d[22]), "+f"(d[23]), "+f"(d[24]), "+f"(d[25]), "+f"(d[26]), "+f"(d[27]) :: "memory");
}

__device__ __forceinline__ void acc_fence(float (&d)[48]) {
  asm volatile("" : "+f"(d[0]), "+f"(d[1]), "+f"(d[2]), "+f"(d[3]), "+f"(d[4]), "+f"(d[5]), "+f"(d[6]), "+f"(d[7]), "+f"(d[8]), "+f"(d[9]), "+f"(d[10]), "+f"(d[11]), "+f"(d[12]), "+f"(d[13]), "+f"(d[14]), "+f"(d[15]), "+f"(d[16]), "+f"(d[17]), "+f"(d[18]), "+f"(d[19]), "+f"(d[20]), "+f"(d[21]), "+f"(d[22]), "+f"(d[23]), "+f"(d[24]), "+f"(d[25]), "+f"(d[26]), "+f"(d[27]), "+f"(d[28]), "+f"(d[29]), "+f"(d[30]), "+f"(d[31]), "+f"(d[32]), "+f"(d[33]), "+f"(d[34]), "+f"(d[35]), "+f"(d[36]), "+f"(d[37]), "+f"(d[38]), "+f"(d[39]), "+f"(d[40]), "+f"(d[41]), "+f"(d[42]), "+f"(d[43]), "+f"(d[44]), "+f"(d[45]), "+f"(d[46]), "+f"(d[47]) :: "memory");
}

constexpr int FW_LD = 200;
__global__ void __launch_bounds__(384) fold_weights_kernel(const __nv_bfloat16* __restrict__ wqkv_t, const __nv_bfloat16* __restrict__ wo_t,
                                    const __nv_bfloat16* __restrict__ wqkv_s, const __nv_bfloat16* __restrict__ wo_s) {
  extern __shared__ __align__(16) uint8_t fsm[];
  __nv_bfloat16* As = reinterpret_cast<__nv_bfloat16*>(fsm);
  float* part = reinterpret_cast<float*>(fsm + CH * FW_LD * 2);
  float* part2 = part + 16 * CH;
  float* cm = part2 + 16 * CH;
  float* Bs = cm + CH;
  const int mat = blockIdx.y, n0 = blockIdx.x * 16, tid = threadIdx.x;
  if (mat == 0 && blockIdx.x == 0 && tid < 32) g_band_cnt[tid] = 0u;
  const __nv_bfloat16* wqkv = (mat < 2) ? wqkv_t : wqkv_s;
  const __nv_bfloat16* wo = (mat < 2) ? wo_t : wo_s;
  const bool isM = (mat & 1) == 0;
  const int offA = isM ? 0 : 2 * CH;
  const int cg = tid % 24, rg = tid / 24;
  {
    uint4 va[12], vb[12];
#pragma unroll
    for (int i = 0; i < 12; i++) va[i] = *reinterpret_cast<const uint4*>(wqkv + (rg * 12 + i) * 3 * CH + offA + cg * 8);
    if (isM) {
#pragma unroll
      for (int i = 0; i < 12; i++) vb[i] = *reinterpret_cast<const uint4*>(wqkv + (rg * 12 + i) * 3 * CH + CH + cg * 8);
    } else {
#pragma unroll
      for (int i = 0; i < 12; i++) vb[i] = make_uint4(0, 0, 0, 0);
    }
    float sa[8] = {0.f, 0.f, 0.f, 0.f, 0.f, 0.f, 0.f, 0.f}, sb[8] = {0.f, 0.f, 0.f, 0.f, 0.f, 0.f, 0.f, 0.f};
#pragma unroll
    for (int i = 0; i < 12; i++) {
      *reinterpret_cast<uint4*>(As + (rg * 12 + i) * FW_LD + cg * 8) = va[i];
      sa[0] += bf_lo(va[i].x); sa[1] += bf_hi(va[i].x); sa[2] += bf_lo(va[i].y); sa[3] += bf_hi(va[i].y);
      sa[4] += bf_lo(va[i].z); sa[5] += bf_hi(va[i].z); sa[6] += bf_lo(va[i].w); sa[7] += bf_hi(va[i].w);
      sb[0] += bf_lo(vb[i].x); sb[1] += bf_hi(vb[i].x); sb[2] += bf_lo(vb[i].y); sb[3] += bf_hi(vb[i].y);
      sb[4] += bf_lo(vb[i].z); sb[5] += bf_hi(vb[i].z); sb[6] += bf_lo(vb[i].w); sb[7] += bf_hi(vb[i].w);
    }
#pragma unroll
    for (int e = 0; e < 8; e++) { part[rg * CH + cg * 8 + e] = sa[e]; part2[rg * CH + cg * 8 + e] = sb[e]; }
  }
  __syncthreads();
  if (tid < CH) {
    float s = 0.f, s2 = 0.f;
#pragma unroll
    for (int r = 0; r < 16; r++) { s += part[r * CH + tid]; s2 += part2[r * CH + tid]; }
    cm[tid] = s * (1.0f / CH);
    const float cmB = s2 * (1.0f / CH);
#pragma unroll
    for (int n = 0; n < 16; n++)
      Bs[n * 196 + tid] = isM ? (__bfloat162float(wqkv[(n0 + n) * 3 * CH + CH + tid]) - cmB) : __bfloat162float(wo[tid * CH + n0 + n]);
  }
  __syncthreads();
  const int k = tid >> 1, nh = (tid & 1) * 8;
  float acc[8];
#pragma unroll
  for (int n = 0; n < 8; n++) acc[n] = 0.f;
#pragma unroll 4
  for (int c = 0; c < CH; c += 4) {
    const uint2 u = *reinterpret_cast<const uint2*>(As + k * FW_LD + c);
    const float4 m4 = *reinterpret_cast<const float4*>(cm + c);
    const float a0 = bf_lo(u.x) - m4.x, a1 = bf_hi(u.x) - m4.y, a2 = bf_lo(u.y) - m4.z, a3 = bf_hi(u.y) - m4.w;
#pragma unroll
    for (int n = 0; n < 8; n++) {
      const float4 b = *reinterpret_cast<const float4*>(Bs + (nh + n) * 196 + c);
      acc[n] = fmaf(a0, b.x, acc[n]); acc[n] = fmaf(a1, b.y, acc[n]);
      acc[n] = fmaf(a2, b.z, acc[n]); acc[n] = fmaf(a3, b.w, acc[n]);
    }
  }
  const int p = k >> 6, kc = k & 63;
#pragma unroll
  for (int n = 0; n < 8; n++) {
    const int nn = n0 + nh + n;
    g_w[mat][p * (CH * 64) + nn * 64 + (((kc >> 3) ^ (nn & 7)) << 3) + (kc & 7)] = __float2bfloat16(acc[n]);
  }
}
constexpr int FW_SMEM = CH * FW_LD * 2 + (32 * CH + CH + 16 * 196) * 4;

struct Params {
  int role;
};

__device__ __forceinline__ uint32_t frag_addr(uint32_t slot_rowoff, uint32_t sw, int hiblk, int kk) {
  const int ci = 2 * kk + hiblk;
  return slot_rowoff + (ci >> 3) * PANEL_X + ((((uint32_t)ci & 7u) ^ sw) << 4);
}

__device__ __forceinline__ float row_rstd(uint32_t slot, int w, int lane) {
  const int row = 16 * w + (lane >> 1), half = lane & 1;
  const uint32_t rbase = slot + row * 128, sw = row & 7;
  float s0 = 0.f, s1 = 0.f, s2 = 0.f, s3 = 0.f, q0 = 0.f, q1 = 0.f, q2 = 0.f, q3 = 0.f;
#pragma unroll
  for (int i = 0; i < 12; i++) {
    const int c = half * 12 + i;
    const uint4 v = lds128(rbase + (c >> 3) * PANEL_X + ((((uint32_t)c & 7u) ^ sw) << 4));
    float lo, hi;
    lo = bf_lo(v.x); hi = bf_hi(v.x); s0 += lo; s1 += hi; q0 = fmaf(lo, lo, q0); q1 = fmaf(hi, hi, q1);
    lo = bf_lo(v.y); hi = bf_hi(v.y); s2 += lo; s3 += hi; q2 = fmaf(lo, lo, q2); q3 = fmaf(hi, hi, q3);
    lo = bf_lo(v.z); hi = bf_hi(v.z); s0 += lo; s1 += hi; q0 = fmaf(lo, lo, q0); q1 = fmaf(hi, hi, q1);
    lo = bf_lo(v.w); hi = bf_hi(v.w); s2 += lo; s3 += hi; q2 = fmaf(lo, lo, q2); q3 = fmaf(hi, hi, q3);
  }
  float s = (s0 + s1) + (s2 + s3), ss = (q0 + q1) + (q2 + q3);
  s += __shfl_xor_sync(0xffffffffu, s, 1);
  ss += __shfl_xor_sync(0xffffffffu, ss, 1);
  const float mean = s * (1.0f / CH);
  const float var = fmaxf(ss * (1.0f / CH) - mean * mean, 0.f);
  return rsqrtf(var + 1e-5f);
}

__global__ void __launch_bounds__(NWG * 128 + 128, 1)
swin_main_kernel(const __grid_constant__ CUtensorMap mapA_in, const __grid_constant__ CUtensorMap mapA_out,
                 const __grid_constant__ CUtensorMap mapB_in, const __grid_constant__ CUtensorMap mapB_out, const int num_a) {
  const int role = (int)blockIdx.x < num_a ? 0 : 1;
  const CUtensorMap* pmap_in = role == 0 ? &mapA_in : &mapB_in;
  const CUtensorMap* pmap_out = role == 0 ? &mapA_out : &mapB_out;
  extern __shared__ __align__(1024) uint8_t smem_raw[];
  const uint32_t sbase = smem_u32(smem_raw);
  const int tid = threadIdx.x, wg = tid >> 7, t128 = tid & 127, w = t128 >> 5, lane = tid & 31;
  const int g = lane >> 2, q = lane & 3;

  const uint32_t bar_w = sbase + SMEM_MISC;
  float* rbuf = reinterpret_cast<float*>(smem_raw + SMEM_RBUF) + wg * 64;

  if (tid == 0) {
    mbar_init(bar_w, 1);
    for (int i = 0; i < NSLOT; i++) { mbar_init(sbase + SMEM_MISC + 8 + 8 * i, 1); mbar_init(sbase + SMEM_MISC + 64 + 8 * i, 128); }
    asm volatile("fence.mbarrier_init.release.cluster;" ::: "memory");
  }
  for (int i = tid; i < NSLOT * SLOT_BYTES / 16; i += NWG * 128 + 128)
    *reinterpret_cast<uint4*>(smem_raw + SMEM_SLOT + i * 16) = make_uint4(0, 0, 0, 0);
  fence_proxy_async();
  __syncthreads();

  const int nunits = role == 0 ? NTILE_A : NUNIT_B;
  const int ustride = role == 0 ? num_a : (int)gridDim.x - num_a;
  const int ubase = role == 0 ? (int)blockIdx.x : (int)blockIdx.x - num_a;
  const int nj = (nunits - ubase + ustride - 1) / ustride;
  const uint32_t tx_bytes = role == 0 ? SLOT_BYTES : 3 * 49 * 128;

  auto coords = [&](int j, int& c1, int& c2, int& c3) {
    const int u = ubase + j * ustride;
    if (role == 0) { c1 = 0; c2 = (u % 14) * 16; c3 = u / 14; }
    else { const int t = u & 3, wx = (u >> 2) & 31, wy = u >> 7; c1 = wx * 7; c2 = wy * 7; c3 = t; }
  };
  auto issue_load = [&](int j) {
    int c1, c2, c3; coords(j, c1, c2, c3);
    if (role != 0) {
      const unsigned int* cnt = &g_band_cnt[c2 / 7];
      unsigned int v; int spins = 0;
      do {
        asm volatile("ld.acquire.gpu.global.u32 %0, [%1];" : "=r"(v) : "l"(cnt) : "memory");
        if (v >= 98u) break;
        __nanosleep(64);
      } while (++spins < (1 << 22));
      asm volatile("fence.proxy.async.global;" ::: "memory");
    }
    const int sl = j % NSLOT;
    const uint32_t bar = sbase + SMEM_MISC + 8 + 8 * sl;
    mbar_expect_tx(bar, tx_bytes);
#pragma unroll
    for (int p = 0; p < 3; p++) tma_load_4d(sbase + SMEM_SLOT + sl * SLOT_BYTES + p * PANEL_X, pmap_in, p * 64, c1, c2, c3, bar);
  };
  auto prefetch_l2 = [&](int j) {
    if (role == 0 && j < nj) {
      int c1, c2, c3; coords(j, c1, c2, c3);
#pragma unroll
      for (int p = 0; p < 3; p++) tma_prefetch_4d(pmap_in, p * 64, c1, c2, c3);
    }
  };

  if (tid >= NWG * 128) {
    asm volatile("setmaxnreg.dec.sync.aligned.u32 40;");
    if (tid == NWG * 128) {
      mbar_expect_tx(bar_w, 2 * WMAT_BYTES);
      bulk_load(sbase + SMEM_W0, &g_w[role * 2][0], WMAT_BYTES, bar_w);
      bulk_load(sbase + SMEM_W1, &g_w[role * 2 + 1][0], WMAT_BYTES, bar_w);
      for (int j = 0; j < NSLOT && j < nj; j++) issue_load(j);
      prefetch_l2(NSLOT); prefetch_l2(NSLOT + 1);
      for (int j = 0; j < nj; j++) {
        const int sl = j % NSLOT;
        mbar_wait(sbase + SMEM_MISC + 64 + 8 * sl, (j / NSLOT) & 1);
        int c1, c2, c3; coords(j, c1, c2, c3);
#pragma unroll
        for (int p = 0; p < 3; p++) tma_store_4d(pmap_out, sbase + SMEM_SLOT + sl * SLOT_BYTES + p * PANEL_X, p * 64, c1, c2, c3);
        bulk_commit();
        bulk_wait_read0();
        if (j + NSLOT < nj) issue_load(j + NSLOT);
        prefetch_l2(j + NSLOT + 2);
        if (role == 0) {
          bulk_wait0();
          asm volatile("fence.proxy.async.global;" ::: "memory");
          __threadfence();
          atomicAdd(&g_band_cnt[c3 / 7], 1u);
        }
      }
      bulk_wait0();
    }
    return;
  }
  asm volatile("setmaxnreg.inc.sync.aligned.u32 232;");
  mbar_wait(bar_w, 0);

  const int blk = lane >> 3;
  const int frow = 16 * w + (lane & 7) + ((blk & 1) << 3);
  const uint32_t fsw = frow & 7;
  const int fhi = blk >> 1;

  const uint64_t dW0 = make_desc(sbase + SMEM_W0, 16, 1024);
  const uint64_t dW1 = make_desc(sbase + SMEM_W1, 16, 1024);

  const float scale_l2e = 0.07216878364870322f * 1.4426950408889634f;

  for (int j = wg; j < nj; j += NWG) {
    const int sl = j % NSLOT;
    const uint32_t slot = sbase + SMEM_SLOT + sl * SLOT_BYTES;
    const uint32_t frowoff = slot + frow * 128;
    const uint64_t dX = make_desc(slot, 16, 1024);
    const uint64_t dXmn = make_desc(slot, PANEL_X, 1024);
    PH(0);
    mbar_wait(sbase + SMEM_MISC + 8 + 8 * sl, (j / NSLOT) & 1);
    PH(1);

    float acc[96];
    wgmma_fence();
#pragma unroll
    for (int kk = 0; kk < 12; kk++) {
      const uint32_t off = (kk >> 2) * PANEL_X + (kk & 3) * 32;
      const uint32_t offw = (kk >> 2) * PANEL_W + (kk & 3) * 32;
      wgmma_n192_ss(acc, dX + (off >> 4), dW0 + (offw >> 4), kk);
    }
    wgmma_commit();
    PH(2);
    const float rmine = row_rstd(slot, w, lane);
    PH(3);
    uint32_t fr[48], xf[48];

    if (role == 0) {
      wgmma_wait0(); acc_fence(acc);
      PH(4);
#pragma unroll
      for (int i = 0; i < 48; i++) fr[i] = pack_bf16(acc[2 * i], acc[2 * i + 1]);
#pragma unroll
      for (int kk = 0; kk < 12; kk++) ldsm_x4(frag_addr(frowoff, fsw, fhi, kk), xf[4 * kk], xf[4 * kk + 1], xf[4 * kk + 2], xf[4 * kk + 3]);
      float d0[4] = {0.f, 0.f, 0.f, 0.f}, d1[4] = {0.f, 0.f, 0.f, 0.f};
      {
        float e0[4] = {0.f, 0.f, 0.f, 0.f}, e1[4] = {0.f, 0.f, 0.f, 0.f};
#pragma unroll
        for (int kk = 0; kk < 12; kk += 2) {
          mma_16816(d0[0], d0[1], d0[2], d0[3], fr[4 * kk], fr[4 * kk + 1], fr[4 * kk + 2], fr[4 * kk + 3], xf[4 * kk], xf[4 * kk + 2]);
          mma_16816(d1[0], d1[1], d1[2], d1[3], fr[4 * kk], fr[4 * kk + 1], fr[4 * kk + 2], fr[4 * kk + 3], xf[4 * kk + 1], xf[4 * kk + 3]);
          mma_16816(e0[0], e0[1], e0[2], e0[3], fr[4 * kk + 4], fr[4 * kk + 5], fr[4 * kk + 6], fr[4 * kk + 7], xf[4 * kk + 4], xf[4 * kk + 6]);
          mma_16816(e1[0], e1[1], e1[2], e1[3], fr[4 * kk + 4], fr[4 * kk + 5], fr[4 * kk + 6], fr[4 * kk + 7], xf[4 * kk + 5], xf[4 * kk + 7]);
        }
#pragma unroll
        for (int i = 0; i < 4; i++) { d0[i] += e0[i]; d1[i] += e1[i]; }
      }
      const float rA = __shfl_sync(0xffffffffu, rmine, 2 * g);
      const float rB = __shfl_sync(0xffffffffu, rmine, 2 * g + 16);
      const float k0 = __shfl_sync(0xffffffffu, rmine, 4 * q);
      const float k1 = __shfl_sync(0xffffffffu, rmine, 4 * q + 2);
      const float k2 = __shfl_sync(0xffffffffu, rmine, 4 * q + 16);
      const float k3 = __shfl_sync(0xffffffffu, rmine, 4 * q + 18);
      const bool valid = (g >> 2) == (q >> 1);
      float sa0 = d0[0] * k0 * (rA * scale_l2e), sa1 = d0[1] * k1 * (rA * scale_l2e);
      float sb0 = d1[2] * k2 * (rB * scale_l2e), sb1 = d1[3] * k3 * (rB * scale_l2e);
      float ma = fmaxf(sa0, sa1), mb = fmaxf(sb0, sb1);
      ma = fmaxf(ma, __shfl_xor_sync(0xffffffffu, ma, 1));
      mb = fmaxf(mb, __shfl_xor_sync(0xffffffffu, mb, 1));
      const float ea0 = exp2f(sa0 - ma), ea1 = exp2f(sa1 - ma);
      const float eb0 = exp2f(sb0 - mb), eb1 = exp2f(sb1 - mb);
      float suma = ea0 + ea1, sumb = eb0 + eb1;
      suma += __shfl_xor_sync(0xffffffffu, suma, 1);
      sumb += __shfl_xor_sync(0xffffffffu, sumb, 1);
      const float ia = __fdividef(1.f, suma), ib = __fdividef(1.f, sumb);
      const uint32_t pa0 = valid ? pack_bf16(ea0 * ia * k0, ea1 * ia * k1) : 0u;
      const uint32_t pa3 = valid ? pack_bf16(eb0 * ib * k2, eb1 * ib * k3) : 0u;
      PH(5);
#pragma unroll
      for (int hh = 0; hh < 2; hh++) {
        uint32_t bt[24];
#pragma unroll
        for (int jj = 0; jj < 6; jj++) ldsm_x4_t(frag_addr(frowoff, fsw, fhi, hh * 6 + jj), bt[4 * jj], bt[4 * jj + 1], bt[4 * jj + 2], bt[4 * jj + 3]);
#pragma unroll
        for (int jj = 0; jj < 6; jj++) {
          const int o = 8 * (hh * 6 + jj);
          acc[o + 0] = 0.f; acc[o + 1] = 0.f; acc[o + 2] = 0.f; acc[o + 3] = 0.f;
          acc[o + 4] = 0.f; acc[o + 5] = 0.f; acc[o + 6] = 0.f; acc[o + 7] = 0.f;
          mma_16816(acc[o + 0], acc[o + 1], acc[o + 2], acc[o + 3], pa0, 0u, 0u, pa3, bt[4 * jj], bt[4 * jj + 1]);
          mma_16816(acc[o + 4], acc[o + 5], acc[o + 6], acc[o + 7], pa0, 0u, 0u, pa3, bt[4 * jj + 2], bt[4 * jj + 3]);
        }
      }
    } else {
      if ((lane & 1) == 0) rbuf[16 * w + (lane >> 1)] = rmine;
      wg_bar(1 + wg);
      wgmma_wait0(); acc_fence(acc);
      PH(4);
#pragma unroll
      for (int i = 0; i < 48; i++) fr[i] = pack_bf16(acc[2 * i], acc[2 * i + 1]);
      float s[28];
      wgmma_fence();
#pragma unroll
      for (int kk = 0; kk < 12; kk++) {
        const uint32_t off = (kk >> 2) * PANEL_X + (kk & 3) * 32;
        wgmma_n56_rs(s, fr[4 * kk], fr[4 * kk + 1], fr[4 * kk + 2], fr[4 * kk + 3], dX + (off >> 4), kk);
      }
      wgmma_commit();
      float rj[14];
#pragma unroll
      for (int j = 0; j < 7; j++) {
        const float2 v = *reinterpret_cast<const float2*>(&rbuf[8 * j + 2 * q]);
        rj[2 * j] = v.x; rj[2 * j + 1] = v.y;
      }
      const float ri0 = rbuf[16 * w + g] * scale_l2e, ri1 = rbuf[16 * w + g + 8] * scale_l2e;
      wgmma_wait0(); acc_fence(s);
      PH(5);
      float m0 = -INFINITY, m1 = -INFINITY;
#pragma unroll
      for (int j = 0; j < 7; j++) {
#pragma unroll
        for (int e = 0; e < 2; e++) {
          const bool ok = (j < 6) || (2 * q + e == 0);
          float v0 = s[4 * j + e] * rj[2 * j + e] * ri0;
          float v1 = s[4 * j + 2 + e] * rj[2 * j + e] * ri1;
          v0 = ok ? v0 : -INFINITY; v1 = ok ? v1 : -INFINITY;
          s[4 * j + e] = v0; s[4 * j + 2 + e] = v1;
          m0 = fmaxf(m0, v0); m1 = fmaxf(m1, v1);
        }
      }
      m0 = fmaxf(m0, __shfl_xor_sync(0xffffffffu, m0, 1)); m0 = fmaxf(m0, __shfl_xor_sync(0xffffffffu, m0, 2));
      m1 = fmaxf(m1, __shfl_xor_sync(0xffffffffu, m1, 1)); m1 = fmaxf(m1, __shfl_xor_sync(0xffffffffu, m1, 2));
      float sum0 = 0.f, sum1 = 0.f;
#pragma unroll
      for (int j = 0; j < 7; j++) {
#pragma unroll
        for (int e = 0; e < 2; e++) {
          const float e0 = exp2f(s[4 * j + e] - m0), e1 = exp2f(s[4 * j + 2 + e] - m1);
          s[4 * j + e] = e0; s[4 * j + 2 + e] = e1;
          sum0 += e0; sum1 += e1;
        }
      }
      sum0 += __shfl_xor_sync(0xffffffffu, sum0, 1); sum0 += __shfl_xor_sync(0xffffffffu, sum0, 2);
      sum1 += __shfl_xor_sync(0xffffffffu, sum1, 1); sum1 += __shfl_xor_sync(0xffffffffu, sum1, 2);
      const float i0 = __fdividef(1.f, sum0), i1 = __fdividef(1.f, sum1);
      uint32_t pa[16];
#pragma unroll
      for (int j = 0; j < 7; j++) {
        pa[(j >> 1) * 4 + (j & 1) * 2 + 0] = pack_bf16(s[4 * j] * i0 * rj[2 * j], s[4 * j + 1] * i0 * rj[2 * j + 1]);
        pa[(j >> 1) * 4 + (j & 1) * 2 + 1] = pack_bf16(s[4 * j + 2] * i1 * rj[2 * j], s[4 * j + 3] * i1 * rj[2 * j + 1]);
      }
      pa[14] = 0u; pa[15] = 0u;
      PH(6);
      wgmma_fence();
#pragma unroll
      for (int kk = 0; kk < 4; kk++)
        wgmma_n192_rs_tb(acc, pa[4 * kk], pa[4 * kk + 1], pa[4 * kk + 2], pa[4 * kk + 3], dXmn + ((kk * 2048) >> 4), kk);
      wgmma_commit();
      wgmma_wait0(); acc_fence(acc);
    }

    PH(7);
#pragma unroll
    for (int i = 0; i < 48; i++) fr[i] = pack_bf16(acc[2 * i], acc[2 * i + 1]);
    wgmma_fence();
#pragma unroll
    for (int kk = 0; kk < 12; kk++) {
      const uint32_t offw = (kk >> 2) * PANEL_W + (kk & 3) * 32;
      wgmma_n192_rs(acc, fr[4 * kk], fr[4 * kk + 1], fr[4 * kk + 2], fr[4 * kk + 3], dW1 + (offw >> 4), kk);
    }
    wgmma_commit();
    if (role != 0) {
#pragma unroll
      for (int kk = 0; kk < 12; kk++) ldsm_x4(frag_addr(frowoff, fsw, fhi, kk), xf[4 * kk], xf[4 * kk + 1], xf[4 * kk + 2], xf[4 * kk + 3]);
    }
    wgmma_wait0(); acc_fence(acc);
    PH(8);
    wg_bar(1 + wg);
    PH(9);
#pragma unroll
    for (int kk = 0; kk < 12; kk++) {
      const uint32_t o0 = add_bf16x2(xf[4 * kk + 0], pack_bf16(acc[8 * kk + 0], acc[8 * kk + 1]));
      const uint32_t o1 = add_bf16x2(xf[4 * kk + 1], pack_bf16(acc[8 * kk + 2], acc[8 * kk + 3]));
      const uint32_t o2 = add_bf16x2(xf[4 * kk + 2], pack_bf16(acc[8 * kk + 4], acc[8 * kk + 5]));
      const uint32_t o3 = add_bf16x2(xf[4 * kk + 3], pack_bf16(acc[8 * kk + 6], acc[8 * kk + 7]));
      stsm_x4(frag_addr(frowoff, fsw, fhi, kk), o0, o1, o2, o3);
    }
    PH(10);
    fence_proxy_async();
    mbar_arrive(sbase + SMEM_MISC + 64 + 8 * sl);
    PH(11);
  }
}

typedef CUresult (*EncodeTiledFn)(CUtensorMap*, CUtensorMapDataType, cuuint32_t, void*, const cuuint64_t*, const cuuint64_t*,
                                  const cuuint32_t*, const cuuint32_t*, CUtensorMapInterleave, CUtensorMapSwizzle,
                                  CUtensorMapL2promotion, CUtensorMapFloatOOBfill);

bool make_map(EncodeTiledFn fn, CUtensorMap* m, void* base, bool pixel_major) {
  cuuint64_t dims[4]; cuuint64_t strides[3]; cuuint32_t box[4]; cuuint32_t es[4] = {1, 1, 1, 1};
  const cuuint64_t sC = (cuuint64_t)CH * 2, sW = sC * WW, sT = sW * HH;
  if (pixel_major) {
    dims[0] = CH; dims[1] = TT; dims[2] = WW; dims[3] = HH;
    strides[0] = sT; strides[1] = sC; strides[2] = sW;
    box[0] = 64; box[1] = 4; box[2] = 16; box[3] = 1;
  } else {
    dims[0] = CH; dims[1] = WW; dims[2] = HH; dims[3] = TT;
    strides[0] = sC; strides[1] = sW; strides[2] = sT;
    box[0] = 64; box[1] = 7; box[2] = 7; box[3] = 1;
  }
  return fn(m, CU_TENSOR_MAP_DATA_TYPE_BFLOAT16, 4, base, dims, strides, box, es, CU_TENSOR_MAP_INTERLEAVE_NONE,
            CU_TENSOR_MAP_SWIZZLE_128B, CU_TENSOR_MAP_L2_PROMOTION_L2_256B, CU_TENSOR_MAP_FLOAT_OOB_FILL_NONE) == CUDA_SUCCESS;
}

}

extern "C" void kernel_launch(void* const* d_in, const int* in_sizes, int n_in, void* d_out, int out_size) {
  const __nv_bfloat16* x = (const __nv_bfloat16*)d_in[0];
  const __nv_bfloat16* wqkv_t = (const __nv_bfloat16*)d_in[1];
  const __nv_bfloat16* wo_t = (const __nv_bfloat16*)d_in[2];
  const __nv_bfloat16* wqkv_s = (const __nv_bfloat16*)d_in[3];
  const __nv_bfloat16* wo_s = (const __nv_bfloat16*)d_in[4];

  static bool init = false;
  static CUtensorMap mA_in, mA_out, mB_in, mB_out;
  static void* last_x = nullptr; static void* last_out = nullptr;
  static int nsm = 132;
  if (!init || last_x != d_in[0] || last_out != d_out) {
    void* fnp = nullptr; cudaDriverEntryPointQueryResult qr;
    cudaGetDriverEntryPoint("cuTensorMapEncodeTiled", &fnp, cudaEnableDefault, &qr);
    EncodeTiledFn fn = (EncodeTiledFn)fnp;
    void* x1p = nullptr; cudaGetSymbolAddress(&x1p, g_x1);
    make_map(fn, &mA_in, (void*)x, true);
    make_map(fn, &mA_out, x1p, true);
    make_map(fn, &mB_in, x1p, false);
    make_map(fn, &mB_out, d_out, false);
    cudaFuncSetAttribute(fold_weights_kernel, cudaFuncAttributeMaxDynamicSharedMemorySize, FW_SMEM);
    cudaFuncSetAttribute(swin_main_kernel, cudaFuncAttributeMaxDynamicSharedMemorySize, SMEM_TOTAL);
    cudaDeviceGetAttribute(&nsm, cudaDevAttrMultiProcessorCount, 0);
    init = true; last_x = d_in[0]; last_out = d_out;
  }
  fold_weights_kernel<<<dim3(12, 4), 384, FW_SMEM>>>(wqkv_t, wo_t, wqkv_s, wo_s);
  swin_main_kernel<<<nsm, NWG * 128 + 128, SMEM_TOTAL>>>(mA_in, mA_out, mB_in, mB_out, NUM_A);
}
```

```cpp
#include <cuda_runtime.h>
#include <cuda_bf16.h>
#include <cuda.h>
#include <stdint.h>

namespace {

constexpr int CH = 192;
constexpr int TT = 4, HH = 224, WW = 224;
constexpr int NTOK = TT * HH * WW;
constexpr int PANEL_X = 64 * 128;
constexpr int SLOT_BYTES = 3 * PANEL_X;
constexpr int PANEL_W = 192 * 128;
constexpr int WMAT_BYTES = 3 * PANEL_W;
constexpr int NWG = 2;
constexpr int NSLOT = 3;
constexpr int SMEM_W0 = 0;
constexpr int SMEM_W1 = WMAT_BYTES;
constexpr int SMEM_SLOT = 2 * WMAT_BYTES;
constexpr int SMEM_MISC = SMEM_SLOT + NSLOT * SLOT_BYTES;
constexpr int SMEM_RBUF = SMEM_MISC + 128;
constexpr int SMEM_TOTAL = SMEM_RBUF + NWG * 64 * 4;

constexpr int NTILE_A = HH * (WW / 16);
constexpr int NUNIT_B = 32 * 32 * 4;
#define NUM_A 56

__device__ __nv_bfloat16 g_x1[(size_t)NTOK * CH];
__device__ unsigned int g_band_cnt[32];
__device__ __align__(1024) __nv_bfloat16 g_w[4][CH * CH];

#define PH(i) do {} while (0)
__device__ __forceinline__ uint32_t smem_u32(const void* p) { return (uint32_t)__cvta_generic_to_shared(p); }

__device__ __forceinline__ void mbar_init(uint32_t bar, uint32_t count) {
  asm volatile("mbarrier.init.shared::cta.b64 [%0], %1;" :: "r"(bar), "r"(count));
}
__device__ __forceinline__ void mbar_expect_tx(uint32_t bar, uint32_t bytes) {
  asm volatile("mbarrier.arrive.expect_tx.shared::cta.b64 _, [%0], %1;" :: "r"(bar), "r"(bytes) : "memory");
}
__device__ __forceinline__ void mbar_arrive(uint32_t bar) {
  asm volatile("mbarrier.arrive.shared::cta.b64 _, [%0];" :: "r"(bar) : "memory");
}
__device__ __forceinline__ void mbar_wait(uint32_t bar, uint32_t parity) {
  asm volatile(
    "{\n.reg .pred p;\n"
    "WAIT_%=:\n"
    "mbarrier.try_wait.parity.shared::cta.b64 p, [%0], %1;\n"
    "@p bra DONE_%=;\n"
    "bra WAIT_%=;\n"
    "DONE_%=:\n}\n" :: "r"(bar), "r"(parity) : "memory");
}
__device__ __forceinline__ void tma_load_4d(uint32_t dst, const CUtensorMap* map, int c0, int c1, int c2, int c3, uint32_t bar) {
  asm volatile("cp.async.bulk.tensor.4d.shared::cluster.global.tile.mbarrier::complete_tx::bytes [%0], [%1, {%2, %3, %4, %5}], [%6];"
    :: "r"(dst), "l"(map), "r"(c0), "r"(c1), "r"(c2), "r"(c3), "r"(bar) : "memory");
}
__device__ __forceinline__ void tma_prefetch_4d(const CUtensorMap* map, int c0, int c1, int c2, int c3) {
  asm volatile("cp.async.bulk.prefetch.tensor.4d.L2.global.tile [%0, {%1, %2, %3, %4}];"
    :: "l"(map), "r"(c0), "r"(c1), "r"(c2), "r"(c3) : "memory");
}
__device__ __forceinline__ void tma_store_4d(const CUtensorMap* map, uint32_t src, int c0, int c1, int c2, int c3) {
  asm volatile("cp.async.bulk.tensor.4d.global.shared::cta.tile.bulk_group [%0, {%1, %2, %3, %4}], [%5];"
    :: "l"(map), "r"(c0), "r"(c1), "r"(c2), "r"(c3), "r"(src) : "memory");
}
__device__ __forceinline__ void bulk_load(uint32_t dst, const void* src, uint32_t bytes, uint32_t bar) {
  asm volatile("cp.async.bulk.shared::cluster.global.mbarrier::complete_tx::bytes [%0], [%1], %2, [%3];"
    :: "r"(dst), "l"(src), "r"(bytes), "r"(bar) : "memory");
}
__device__ __forceinline__ void bulk_commit() { asm volatile("cp.async.bulk.commit_group;" ::: "memory"); }
__device__ __forceinline__ void bulk_wait_read0() { asm volatile("cp.async.bulk.wait_group.read 0;" ::: "memory"); }
__device__ __forceinline__ void bulk_wait0() { asm volatile("cp.async.bulk.wait_group 0;" ::: "memory"); }
__device__ __forceinline__ void fence_proxy_async() { asm volatile("fence.proxy.async.shared::cta;" ::: "memory"); }
__device__ __forceinline__ void wg_bar(int id) { asm volatile("bar.sync %0, 128;" :: "r"(id) : "memory"); }
__device__ __forceinline__ void wgmma_fence() { asm volatile("wgmma.fence.sync.aligned;" ::: "memory"); }
__device__ __forceinline__ void wgmma_commit() { asm volatile("wgmma.commit_group.sync.aligned;" ::: "memory"); }
__device__ __forceinline__ void wgmma_wait0() { asm volatile("wgmma.wait_group.sync.aligned 0;" ::: "memory"); }

__device__ __forceinline__ uint64_t make_desc(uint32_t saddr, uint32_t lbo, uint32_t sbo) {
  return (uint64_t)((saddr & 0x3FFFF) >> 4) | ((uint64_t)((lbo & 0x3FFFF) >> 4) << 16) |
         ((uint64_t)((sbo & 0x3FFFF) >> 4) << 32) | ((uint64_t)1 << 62);
}
__device__ __forceinline__ uint32_t pack_bf16(float lo, float hi) {
  uint32_t r; asm("cvt.rn.bf16x2.f32 %0, %1, %2;" : "=r"(r) : "f"(hi), "f"(lo)); return r;
}
__device__ __forceinline__ uint32_t add_bf16x2(uint32_t a, uint32_t b) {
  uint32_t r; asm("add.rn.bf16x2 %0, %1, %2;" : "=r"(r) : "r"(a), "r"(b)); return r;
}
__device__ __forceinline__ float bf_lo(uint32_t u) { return __uint_as_float(u << 16); }
__device__ __forceinline__ float bf_hi(uint32_t u) { return __uint_as_float(u & 0xffff0000u); }
__device__ __forceinline__ void ldsm_x4(uint32_t addr, uint32_t& r0, uint32_t& r1, uint32_t& r2, uint32_t& r3) {
  asm volatile("ldmatrix.sync.aligned.m8n8.x4.shared.b16 {%0,%1,%2,%3}, [%4];"
    : "=r"(r0), "=r"(r1), "=r"(r2), "=r"(r3) : "r"(addr) : "memory");
}
__device__ __forceinline__ void ldsm_x4_t(uint32_t addr, uint32_t& r0, uint32_t& r1, uint32_t& r2, uint32_t& r3) {
  asm volatile("ldmatrix.sync.aligned.m8n8.x4.trans.shared.b16 {%0,%1,%2,%3}, [%4];"
    : "=r"(r0), "=r"(r1), "=r"(r2), "=r"(r3) : "r"(addr) : "memory");
}
__device__ __forceinline__ void stsm_x4(uint32_t addr, uint32_t r0, uint32_t r1, uint32_t r2, uint32_t r3) {
  asm volatile("stmatrix.sync.aligned.m8n8.x4.shared.b16 [%0], {%1,%2,%3,%4};"
    :: "r"(addr), "r"(r0), "r"(r1), "r"(r2), "r"(r3) : "memory");
}
__device__ __forceinline__ void mma_16816(float& d0, float& d1, float& d2, float& d3,
                                          uint32_t a0, uint32_t a1, uint32_t a2, uint32_t a3, uint32_t b0, uint32_t b1) {
  asm volatile("mma.sync.aligned.m16n8k16.row.col.f32.bf16.bf16.f32 {%0,%1,%2,%3}, {%4,%5,%6,%7}, {%8,%9}, {%0,%1,%2,%3};"
    : "+f"(d0), "+f"(d1), "+f"(d2), "+f"(d3) : "r"(a0), "r"(a1), "r"(a2), "r"(a3), "r"(b0), "r"(b1));
}
__device__ __forceinline__ uint4 lds128(uint32_t addr) {
  uint4 v; asm volatile("ld.shared.v4.u32 {%0,%1,%2,%3}, [%4];" : "=r"(v.x), "=r"(v.y), "=r"(v.z), "=r"(v.w) : "r"(addr) : "memory");
  return v;
}

__device__ __forceinline__ void wgmma_n192_ss(float (&d)[96], uint64_t da, uint64_t db, int scale_d) {
  asm volatile("{\n.reg .pred p;\nsetp.ne.b32 p, %98, 0;\n"
    "wgmma.mma_async.sync.aligned.m64n192k16.f32.bf16.bf16 {%0, %1, %2, %3, %4, %5, %6, %7, %8, %9, %10, %11, %12, %13, %14, %15, %16, %17, %18, %19, %20, %21, %22, %23, %24, %25, %26, %27, %28, %29, %30, %31, %32, %33, %34, %35, %36, %37, %38, %39, %40, %41, %42, %43, %44, %45, %46, %47, %48, %49, %50, %51, %52, %53, %54, %55, %56, %57, %58, %59, %60, %61, %62, %63, %64, %65, %66, %67, %68, %69, %70, %71, %72, %73, %74, %75, %76, %77, %78, %79, %80, %81, %82, %83, %84, %85, %86, %87, %88, %89, %90, %91, %92, %93, %94, %95}, %96, %97, p, 1, 1, 0, 0;\n}\n"
    : "+f"(d[0]), "+f"(d[1]), "+f"(d[2]), "+f"(d[3]), "+f"(d[4]), "+f"(d[5]), "+f"(d[6]), "+f"(d[7]), "+f"(d[8]), "+f"(d[9]), "+f"(d[10]), "+f"(d[11]), "+f"(d[12]), "+f"(d[13]), "+f"(d[14]), "+f"(d[15]), "+f"(d[16]), "+f"(d[17]), "+f"(d[18]), "+f"(d[19]), "+f"(d[20]), "+f"(d[21]), "+f"(d[22]), "+f"(d[23]), "+f"(d[24]), "+f"(d[25]), "+f"(d[26]), "+f"(d[27]), "+f"(d[28]), "+f"(d[29]), "+f"(d[30]), "+f"(d[31]), "+f"(d[32]), "+f"(d[33]), "+f"(d[34]), "+f"(d[35]), "+f"(d[36]), "+f"(d[37]), "+f"(d[38]), "+f"(d[39]), "+f"(d[40]), "+f"(d[41]), "+f"(d[42]), "+f"(d[43]), "+f"(d[44]), "+f"(d[45]), "+f"(d[46]), "+f"(d[47]), "+f"(d[48]), "+f"(d[49]), "+f"(d[50]), "+f"(d[51]), "+f"(d[52]), "+f"(d[53]), "+f"(d[54]), "+f"(d[55]), "+f"(d[56]), "+f"(d[57]), "+f"(d[58]), "+f"(d[59]), "+f"(d[60]), "+f"(d[61]), "+f"(d[62]), "+f"(d[63]), "+f"(d[64]), "+f"(d[65]), "+f"(d[66]), "+f"(d[67]), "+f"(d[68]), "+f"(d[69]), "+f"(d[70]), "+f"(d[71]), "+f"(d[72]), "+f"(d[73]), "+f"(d[74]), "+f"(d[75]), "+f"(d[76]), "+f"(d[77]), "+f"(d[78]), "+f"(d[79]), "+f"(d[80]), "+f"(d[81]), "+f"(d[82]), "+f"(d[83]), "+f"(d[84]), "+f"(d[85]), "+f"(d[86]), "+f"(d[87]), "+f"(d[88]), "+f"(d[89]), "+f"(d[90]), "+f"(d[91]), "+f"(d[92]), "+f"(d[93]), "+f"(d[94]), "+f"(d[95])
    : "l"(da), "l"(db), "r"(scale_d));
}

__device__ __forceinline__ void wgmma_n192_rs(float (&d)[96], uint32_t a0, uint32_t a1, uint32_t a2, uint32_t a3, uint64_t db, int scale_d) {
  asm volatile("{\n.reg .pred p;\nsetp.ne.b32 p, %101, 0;\n"
    "wgmma.mma_async.sync.aligned.m64n192k16.f32.bf16.bf16 {%0, %1, %2, %3, %4, %5, %6, %7, %8, %9, %10, %11, %12, %13, %14, %15, %16, %17, %18, %19, %20, %21, %22, %23, %24, %25, %26, %27, %28, %29, %30, %31, %32, %33, %34, %35, %36, %37, %38, %39, %40, %41, %42, %43, %44, %45, %46, %47, %48, %49, %50, %51, %52, %53, %54, %55, %56, %57, %58, %59, %60, %61, %62, %63, %64, %65, %66, %67, %68, %69, %70, %71, %72, %73, %74, %75, %76, %77, %78, %79, %80, %81, %82, %83, %84, %85, %86, %87, %88, %89, %90, %91, %92, %93, %94, %95}, {%96, %97, %98, %99}, %100, p, 1, 1, 0;\n}\n"
    : "+f"(d[0]), "+f"(d[1]), "+f"(d[2]), "+f"(d[3]), "+f"(d[4]), "+f"(d[5]), "+f"(d[6]), "+f"(d[7]), "+f"(d[8]), "+f"(d[9]), "+f"(d[10]), "+f"(d[11]), "+f"(d[12]), "+f"(d[13]), "+f"(d[14]), "+f"(d[15]), "+f"(d[16]), "+f"(d[17]), "+f"(d[18]), "+f"(d[19]), "+f"(d[20]), "+f"(d[21]), "+f"(d[22]), "+f"(d[23]), "+f"(d[24]), "+f"(d[25]), "+f"(d[26]), "+f"(d[27]), "+f"(d[28]), "+f"(d[29]), "+f"(d[30]), "+f"(d[31]), "+f"(d[32]), "+f"(d[33]), "+f"(d[34]), "+f"(d[35]), "+f"(d[36]), "+f"(d[37]), "+f"(d[38]), "+f"(d[39]), "+f"(d[40]), "+f"(d[41]), "+f"(d[42]), "+f"(d[43]), "+f"(d[44]), "+f"(d[45]), "+f"(d[46]), "+f"(d[47]), "+f"(d[48]), "+f"(d[49]), "+f"(d[50]), "+f"(d[51]), "+f"(d[52]), "+f"(d[53]), "+f"(d[54]), "+f"(d[55]), "+f"(d[56]), "+f"(d[57]), "+f"(d[58]), "+f"(d[59]), "+f"(d[60]), "+f"(d[61]), "+f"(d[62]), "+f"(d[63]), "+f"(d[64]), "+f"(d[65]), "+f"(d[66]), "+f"(d[67]), "+f"(d[68]), "+f"(d[69]), "+f"(d[70]), "+f"(d[71]), "+f"(d[72]), "+f"(d[73]), "+f"(d[74]), "+f"(d[75]), "+f"(d[76]), "+f"(d[77]), "+f"(d[78]), "+f"(d[79]), "+f"(d[80]), "+f"(d[81]), "+f"(d[82]), "+f"(d[83]), "+f"(d[84]), "+f"(d[85]), "+f"(d[86]), "+f"(d[87]), "+f"(d[88]), "+f"(d[89]), "+f"(d[90]), "+f"(d[91]), "+f"(d[92]), "+f"(d[93]), "+f"(d[94]), "+f"(d[95])
    : "r"(a0), "r"(a1), "r"(a2), "r"(a3), "l"(db), "r"(scale_d));
}

__device__ __forceinline__ void wgmma_n192_rs_tb(float (&d)[96], uint32_t a0, uint32_t a1, uint32_t a2, uint32_t a3, uint64_t db, int scale_d) {
  asm volatile("{\n.reg .pred p;\nsetp.ne.b32 p, %101, 0;\n"
    "wgmma.mma_async.sync.aligned.m64n192k16.f32.bf16.bf16 {%0, %1, %2, %3, %4, %5, %6, %7, %8, %9, %10, %11, %12, %13, %14, %15, %16, %17, %18, %19, %20, %21, %22, %23, %24, %25, %26, %27, %28, %29, %30, %31, %32, %33, %34, %35, %36, %37, %38, %39, %40, %41, %42, %43, %44, %45, %46, %47, %48, %49, %50, %51, %52, %53, %54, %55, %56, %57, %58, %59, %60, %61, %62, %63, %64, %65, %66, %67, %68, %69, %70, %71, %72, %73, %74, %75, %76, %77, %78, %79, %80, %81, %82, %83, %84, %85, %86, %87, %88, %89, %90, %91, %92, %93, %94, %95}, {%96, %97, %98, %99}, %100, p, 1, 1, 1;\n}\n"
    : "+f"(d[0]), "+f"(d[1]), "+f"(d[2]), "+f"(d[3]), "+f"(d[4]), "+f"(d[5]), "+f"(d[6]), "+f"(d[7]), "+f"(d[8]), "+f"(d[9]), "+f"(d[10]), "+f"(d[11]), "+f"(d[12]), "+f"(d[13]), "+f"(d[14]), "+f"(d[15]), "+f"(d[16]), "+f"(d[17]), "+f"(d[18]), "+f"(d[19]), "+f"(d[20]), "+f"(d[21]), "+f"(d[22]), "+f"(d[23]), "+f"(d[24]), "+f"(d[25]), "+f"(d[26]), "+f"(d[27]), "+f"(d[28]), "+f"(d[29]), "+f"(d[30]), "+f"(d[31]), "+f"(d[32]), "+f"(d[33]), "+f"(d[34]), "+f"(d[35]), "+f"(d[36]), "+f"(d[37]), "+f"(d[38]), "+f"(d[39]), "+f"(d[40]), "+f"(d[41]), "+f"(d[42]), "+f"(d[43]), "+f"(d[44]), "+f"(d[45]), "+f"(d[46]), "+f"(d[47]), "+f"(d[48]), "+f"(d[49]), "+f"(d[50]), "+f"(d[51]), "+f"(d[52]), "+f"(d[53]), "+f"(d[54]), "+f"(d[55]), "+f"(d[56]), "+f"(d[57]), "+f"(d[58]), "+f"(d[59]), "+f"(d[60]), "+f"(d[61]), "+f"(d[62]), "+f"(d[63]), "+f"(d[64]), "+f"(d[65]), "+f"(d[66]), "+f"(d[67]), "+f"(d[68]), "+f"(d[69]), "+f"(d[70]), "+f"(d[71]), "+f"(d[72]), "+f"(d[73]), "+f"(d[74]), "+f"(d[75]), "+f"(d[76]), "+f"(d[77]), "+f"(d[78]), "+f"(d[79]), "+f"(d[80]), "+f"(d[81]), "+f"(d[82]), "+f"(d[83]), "+f"(d[84]), "+f"(d[85]), "+f"(d[86]), "+f"(d[87]), "+f"(d[88]), "+f"(d[89]), "+f"(d[90]), "+f"(d[91]), "+f"(d[92]), "+f"(d[93]), "+f"(d[94]), "+f"(d[95])
    : "r"(a0), "r"(a1), "r"(a2), "r"(a3), "l"(db), "r"(scale_d));
}

__device__ __forceinline__ void wgmma_n56_rs(float (&d)[28], uint32_t a0, uint32_t a1, uint32_t a2, uint32_t a3, uint64_t db, int scale_d) {
  asm volatile("{\n.reg .pred p;\nsetp.ne.b32 p, %33, 0;\n"
    "wgmma.mma_async.sync.aligned.m64n56k16.f32.bf16.bf16 {%0, %1, %2, %3, %4, %5, %6, %7, %8, %9, %10, %11, %12, %13, %14, %15, %16, %17, %18, %19, %20, %21, %22, %23, %24, %25, %26, %27}, {%28, %29, %30, %31}, %32, p, 1, 1, 0;\n}\n"
    : "+f"(d[0]), "+f"(d[1]), "+f"(d[2]), "+f"(d[3]), "+f"(d[4]), "+f"(d[5]), "+f"(d[6]), "+f"(d[7]), "+f"(d[8]), "+f"(d[9]), "+f"(d[10]), "+f"(d[11]), "+f"(d[12]), "+f"(d[13]), "+f"(d[14]), "+f"(d[15]), "+f"(d[16]), "+f"(d[17]), "+f"(d[18]), "+f"(d[19]), "+f"(d[20]), "+f"(d[21]), "+f"(d[22]), "+f"(d[23]), "+f"(d[24]), "+f"(d[25]), "+f"(d[26]), "+f"(d[27])
    : "r"(a0), "r"(a1), "r"(a2), "r"(a3), "l"(db), "r"(scale_d));
}

__device__ __forceinline__ void wgmma_n96_rs(float (&d)[48], uint32_t a0, uint32_t a1, uint32_t a2, uint32_t a3, uint64_t db, int scale_d) {
  asm volatile("{\n.reg .pred p;\nsetp.ne.b32 p, %53, 0;\n"
    "wgmma.mma_async.sync.aligned.m64n96k16.f32.bf16.bf16 {%0, %1, %2, %3, %4, %5, %6, %7, %8, %9, %10, %11, %12, %13, %14, %15, %16, %17, %18, %19, %20, %21, %22, %23, %24, %25, %26, %27, %28, %29, %30, %31, %32, %33, %34, %35, %36, %37, %38, %39, %40, %41, %42, %43, %44, %45, %46, %47}, {%48, %49, %50, %51}, %52, p, 1, 1, 0;\n}\n"
    : "+f"(d[0]), "+f"(d[1]), "+f"(d[2]), "+f"(d[3]), "+f"(d[4]), "+f"(d[5]), "+f"(d[6]), "+f"(d[7]), "+f"(d[8]), "+f"(d[9]), "+f"(d[10]), "+f"(d[11]), "+f"(d[12]), "+f"(d[13]), "+f"(d[14]), "+f"(d[15]), "+f"(d[16]), "+f"(d[17]), "+f"(d[18]), "+f"(d[19]), "+f"(d[20]), "+f"(d[21]), "+f"(d[22]), "+f"(d[23]), "+f"(d[24]), "+f"(d[25]), "+f"(d[26]), "+f"(d[27]), "+f"(d[28]), "+f"(d[29]), "+f"(d[30]), "+f"(d[31]), "+f"(d[32]), "+f"(d[33]), "+f"(d[34]), "+f"(d[35]), "+f"(d[36]), "+f"(d[37]), "+f"(d[38]), "+f"(d[39]), "+f"(d[40]), "+f"(d[41]), "+f"(d[42]), "+f"(d[43]), "+f"(d[44]), "+f"(d[45]), "+f"(d[46]), "+f"(d[47])
    : "r"(a0), "r"(a1), "r"(a2), "r"(a3), "l"(db), "r"(scale_d));
}

__device__ __forceinline__ void acc_fence(float (&d)[96]) {
  asm volatile("" : "+f"(d[0]), "+f"(d[1]), "+f"(d[2]), "+f"(d[3]), "+f"(d[4]), "+f"(d[5]), "+f"(d[6]), "+f"(d[7]), "+f"(d[8]), "+f"(d[9]), "+f"(d[10]), "+f"(d[11]), "+f"(d[12]), "+f"(d[13]), "+f"(d[14]), "+f"(d[15]), "+f"(d[16]), "+f"(d[17]), "+f"(d[18]), "+f"(d[19]), "+f"(d[20]), "+f"(d[21]), "+f"(d[22]), "+f"(d[23]), "+f"(d[24]), "+f"(d[25]), "+f"(d[26]), "+f"(d[27]), "+f"(d[28]), "+f"(d[29]), "+f"(d[30]), "+f"(d[31]), "+f"(d[32]), "+f"(d[33]), "+f"(d[34]), "+f"(d[35]), "+f"(d[36]), "+f"(d[37]), "+f"(d[38]), "+f"(d[39]), "+f"(d[40]), "+f"(d[41]), "+f"(d[42]), "+f"(d[43]), "+f"(d[44]), "+f"(d[45]), "+f"(d[46]), "+f"(d[47]), "+f"(d[48]), "+f"(d[49]), "+f"(d[50]), "+f"(d[51]), "+f"(d[52]), "+f"(d[53]), "+f"(d[54]), "+f"(d[55]), "+f"(d[56]), "+f"(d[57]), "+f"(d[58]), "+f"(d[59]), "+f"(d[60]), "+f"(d[61]), "+f"(d[62]), "+f"(d[63]), "+f"(d[64]), "+f"(d[65]), "+f"(d[66]), "+f"(d[67]), "+f"(d[68]), "+f"(d[69]), "+f"(d[70]), "+f"(d[71]), "+f"(d[72]), "+f"(d[73]), "+f"(d[74]), "+f"(d[75]), "+f"(d[76]), "+f"(d[77]), "+f"(d[78]), "+f"(d[79]), "+f"(d[80]), "+f"(d[81]), "+f"(d[82]), "+f"(d[83]), "+f"(d[84]), "+f"(d[85]), "+f"(d[86]), "+f"(d[87]), "+f"(d[88]), "+f"(d[89]), "+f"(d[90]), "+f"(d[91]), "+f"(d[92]), "+f"(d[93]), "+f"(d[94]), "+f"(d[95]) :: "memory");
}

__device__ __forceinline__ void acc_fence(float (&d)[28]) {
  asm volatile("" : "+f"(d[0]), "+f"(d[1]), "+f"(d[2]), "+f"(d[3]), "+f"(d[4]), "+f"(d[5]), "+f"(d[6]), "+f"(d[7]), "+f"(d[8]), "+f"(d[9]), "+f"(d[10]), "+f"(d[11]), "+f"(d[12]), "+f"(d[13]), "+f"(d[14]), "+f"(d[15]), "+f"(d[16]), "+f"(d[17]), "+f"(d[18]), "+f"(d[19]), "+f"(d[20]), "+f"(d[21]), "+f"(d[22]), "+f"(d[23]), "+f"(d[24]), "+f"(d[25]), "+f"(d[26]), "+f"(d[27]) :: "memory");
}

__device__ __forceinline__ void acc_fence(float (&d)[48]) {
  asm volatile("" : "+f"(d[0]), "+f"(d[1]), "+f"(d[2]), "+f"(d[3]), "+f"(d[4]), "+f"(d[5]), "+f"(d[6]), "+f"(d[7]), "+f"(d[8]), "+f"(d[9]), "+f"(d[10]), "+f"(d[11]), "+f"(d[12]), "+f"(d[13]), "+f"(d[14]), "+f"(d[15]), "+f"(d[16]), "+f"(d[17]), "+f"(d[18]), "+f"(d[19]), "+f"(d[20]), "+f"(d[21]), "+f"(d[22]), "+f"(d[23]), "+f"(d[24]), "+f"(d[25]), "+f"(d[26]), "+f"(d[27]), "+f"(d[28]), "+f"(d[29]), "+f"(d[30]), "+f"(d[31]), "+f"(d[32]), "+f"(d[33]), "+f"(d[34]), "+f"(d[35]), "+f"(d[36]), "+f"(d[37]), "+f"(d[38]), "+f"(d[39]), "+f"(d[40]), "+f"(d[41]), "+f"(d[42]), "+f"(d[43]), "+f"(d[44]), "+f"(d[45]), "+f"(d[46]), "+f"(d[47]) :: "memory");
}

constexpr int FW_LD = 200;
__global__ void __launch_bounds__(384) fold_weights_kernel(const __nv_bfloat16* __restrict__ wqkv_t, const __nv_bfloat16* __restrict__ wo_t,
                                    const __nv_bfloat16* __restrict__ wqkv_s, const __nv_bfloat16* __restrict__ wo_s) {
  extern __shared__ __align__(16) uint8_t fsm[];
  __nv_bfloat16* As = reinterpret_cast<__nv_bfloat16*>(fsm);
  float* part = reinterpret_cast<float*>(fsm + CH * FW_LD * 2);
  float* part2 = part + 16 * CH;
  float* cm = part2 + 16 * CH;
  float* Bs = cm + CH;
  const int mat = blockIdx.y, n0 = blockIdx.x * 16, tid = threadIdx.x;
  if (mat == 0 && blockIdx.x == 0 && tid < 32) g_band_cnt[tid] = 0u;
  const __nv_bfloat16* wqkv = (mat < 2) ? wqkv_t : wqkv_s;
  const __nv_bfloat16* wo = (mat < 2) ? wo_t : wo_s;
  const bool isM = (mat & 1) == 0;
  const int offA = isM ? 0 : 2 * CH;
  const int cg = tid % 24, rg = tid / 24;
  {
    uint4 va[12], vb[12];
#pragma unroll
    for (int i = 0; i < 12; i++) va[i] = *reinterpret_cast<const uint4*>(wqkv + (rg * 12 + i) * 3 * CH + offA + cg * 8);
    if (isM) {
#pragma unroll
      for (int i = 0; i < 12; i++) vb[i] = *reinterpret_cast<const uint4*>(wqkv + (rg * 12 + i) * 3 * CH + CH + cg * 8);
    } else {
#pragma unroll
      for (int i = 0; i < 12; i++) vb[i] = make_uint4(0, 0, 0, 0);
    }
    float sa[8] = {0.f, 0.f, 0.f, 0.f, 0.f, 0.f, 0.f, 0.f}, sb[8] = {0.f, 0.f, 0.f, 0.f, 0.f, 0.f, 0.f, 0.f};
#pragma unroll
    for (int i = 0; i < 12; i++) {
      *reinterpret_cast<uint4*>(As + (rg * 12 + i) * FW_LD + cg * 8) = va[i];
      sa[0] += bf_lo(va[i].x); sa[1] += bf_hi(va[i].x); sa[2] += bf_lo(va[i].y); sa[3] += bf_hi(va[i].y);
      sa[4] += bf_lo(va[i].z); sa[5] += bf_hi(va[i].z); sa[6] += bf_lo(va[i].w); sa[7] += bf_hi(va[i].w);
      sb[0] += bf_lo(vb[i].x); sb[1] += bf_hi(vb[i].x); sb[2] += bf_lo(vb[i].y); sb[3] += bf_hi(vb[i].y);
      sb[4] += bf_lo(vb[i].z); sb[5] += bf_hi(vb[i].z); sb[6] += bf_lo(vb[i].w); sb[7] += bf_hi(vb[i].w);
    }
#pragma unroll
    for (int e = 0; e < 8; e++) { part[rg * CH + cg * 8 + e] = sa[e]; part2[rg * CH + cg * 8 + e] = sb[e]; }
  }
  __syncthreads();
  if (tid < CH) {
    float s = 0.f, s2 = 0.f;
#pragma unroll
    for (int r = 0; r < 16; r++) { s += part[r * CH + tid]; s2 += part2[r * CH + tid]; }
    cm[tid] = s * (1.0f / CH);
    const float cmB = s2 * (1.0f / CH);
#pragma unroll
    for (int n = 0; n < 16; n++)
      Bs[n * 196 + tid] = isM ? (__bfloat162float(wqkv[(n0 + n) * 3 * CH + CH + tid]) - cmB) : __bfloat162float(wo[tid * CH + n0 + n]);
  }
  __syncthreads();
  const int k = tid >> 1, nh = (tid & 1) * 8;
  float acc[8];
#pragma unroll
  for (int n = 0; n < 8; n++) acc[n] = 0.f;
#pragma unroll 4
  for (int c = 0; c < CH; c += 4) {
    const uint2 u = *reinterpret_cast<const uint2*>(As + k * FW_LD + c);
    const float4 m4 = *reinterpret_cast<const float4*>(cm + c);
    const float a0 = bf_lo(u.x) - m4.x, a1 = bf_hi(u.x) - m4.y, a2 = bf_lo(u.y) - m4.z, a3 = bf_hi(u.y) - m4.w;
#pragma unroll
    for (int n = 0; n < 8; n++) {
      const float4 b = *reinterpret_cast<const float4*>(Bs + (nh + n) * 196 + c);
      acc[n] = fmaf(a0, b.x, acc[n]); acc[n] = fmaf(a1, b.y, acc[n]);
      acc[n] = fmaf(a2, b.z, acc[n]); acc[n] = fmaf(a3, b.w, acc[n]);
    }
  }
  const int p = k >> 6, kc = k & 63;
#pragma unroll
  for (int n = 0; n < 8; n++) {
    const int nn = n0 + nh + n;
    g_w[mat][p * (CH * 64) + nn * 64 + (((kc >> 3) ^ (nn & 7)) << 3) + (kc & 7)] = __float2bfloat16(acc[n]);
  }
}
constexpr int FW_SMEM = CH * FW_LD * 2 + (32 * CH + CH + 16 * 196) * 4;

struct Params {
  int role;
};

__device__ __forceinline__ uint32_t frag_addr(uint32_t slot_rowoff, uint32_t sw, int hiblk, int kk) {
  const int ci = 2 * kk + hiblk;
  return slot_rowoff + (ci >> 3) * PANEL_X + ((((uint32_t)ci & 7u) ^ sw) << 4);
}

__device__ __forceinline__ float row_rstd(uint32_t slot, int w, int lane) {
  const int row = 16 * w + (lane >> 1), half = lane & 1;
  const uint32_t rbase = slot + row * 128, sw = row & 7;
  float s0 = 0.f, s1 = 0.f, s2 = 0.f, s3 = 0.f, q0 = 0.f, q1 = 0.f, q2 = 0.f, q3 = 0.f;
#pragma unroll
  for (int i = 0; i < 12; i++) {
    const int c = half * 12 + i;
    const uint4 v = lds128(rbase + (c >> 3) * PANEL_X + ((((uint32_t)c & 7u) ^ sw) << 4));
    float lo, hi;
    lo = bf_lo(v.x); hi = bf_hi(v.x); s0 += lo; s1 += hi; q0 = fmaf(lo, lo, q0); q1 = fmaf(hi, hi, q1);
    lo = bf_lo(v.y); hi = bf_hi(v.y); s2 += lo; s3 += hi; q2 = fmaf(lo, lo, q2); q3 = fmaf(hi, hi, q3);
    lo = bf_lo(v.z); hi = bf_hi(v.z); s0 += lo; s1 += hi; q0 = fmaf(lo, lo, q0); q1 = fmaf(hi, hi, q1);
    lo = bf_lo(v.w); hi = bf_hi(v.w); s2 += lo; s3 += hi; q2 = fmaf(lo, lo, q2); q3 = fmaf(hi, hi, q3);
  }
  float s = (s0 + s1) + (s2 + s3), ss = (q0 + q1) + (q2 + q3);
  s += __shfl_xor_sync(0xffffffffu, s, 1);
  ss += __shfl_xor_sync(0xffffffffu, ss, 1);
  const float mean = s * (1.0f / CH);
  const float var = fmaxf(ss * (1.0f / CH) - mean * mean, 0.f);
  return rsqrtf(var + 1e-5f);
}

__global__ void __launch_bounds__(NWG * 128 + 128, 1)
swin_main_kernel(const __grid_constant__ CUtensorMap mapA_in, const __grid_constant__ CUtensorMap mapA_out,
                 const __grid_constant__ CUtensorMap mapB_in, const __grid_constant__ CUtensorMap mapB_out, const int num_a) {
  const int role = (int)blockIdx.x < num_a ? 0 : 1;
  const CUtensorMap* pmap_in = role == 0 ? &mapA_in : &mapB_in;
  const CUtensorMap* pmap_out = role == 0 ? &mapA_out : &mapB_out;
  extern __shared__ __align__(1024) uint8_t smem_raw[];
  const uint32_t sbase = smem_u32(smem_raw);
  const int tid = threadIdx.x, wg = tid >> 7, t128 = tid & 127, w = t128 >> 5, lane = tid & 31;
  const int g = lane >> 2, q = lane & 3;

  const uint32_t bar_w = sbase + SMEM_MISC;
  float* rbuf = reinterpret_cast<float*>(smem_raw + SMEM_RBUF) + wg * 64;

  if (tid == 0) {
    mbar_init(bar_w, 1);
    for (int i = 0; i < NSLOT; i++) { mbar_init(sbase + SMEM_MISC + 8 + 8 * i, 1); mbar_init(sbase + SMEM_MISC + 64 + 8 * i, 128); }
    asm volatile("fence.mbarrier_init.release.cluster;" ::: "memory");
  }
  for (int i = tid; i < NSLOT * SLOT_BYTES / 16; i += NWG * 128 + 128)
    *reinterpret_cast<uint4*>(smem_raw + SMEM_SLOT + i * 16) = make_uint4(0, 0, 0, 0);
  fence_proxy_async();
  __syncthreads();

  const int nunits = role == 0 ? NTILE_A : NUNIT_B;
  const int ustride = role == 0 ? num_a : (int)gridDim.x - num_a;
  const int ubase = role == 0 ? (int)blockIdx.x : (int)blockIdx.x - num_a;
  const int nj = (nunits - ubase + ustride - 1) / ustride;
  const uint32_t tx_bytes = role == 0 ? SLOT_BYTES : 3 * 49 * 128;

  auto coords = [&](int j, int& c1, int& c2, int& c3) {
    const int u = ubase + j * ustride;
    if (role == 0) { c1 = 0; c2 = (u % 14) * 16; c3 = u / 14; }
    else { const int t = u & 3, wx = (u >> 2) & 31, wy = u >> 7; c1 = wx * 7; c2 = wy * 7; c3 = t; }
  };
  auto issue_load = [&](int j) {
    int c1, c2, c3; coords(j, c1, c2, c3);
    if (role != 0) {
      const unsigned int* cnt = &g_band_cnt[c2 / 7];
      unsigned int v; int spins = 0;
      do {
        asm volatile("ld.acquire.gpu.global.u32 %0, [%1];" : "=r"(v) : "l"(cnt) : "memory");
        if (v >= 98u) break;
        __nanosleep(64);
      } while (++spins < (1 << 22));
      asm volatile("fence.proxy.async.global;" ::: "memory");
    }
    const int sl = j % NSLOT;
    const uint32_t bar = sbase + SMEM_MISC + 8 + 8 * sl;
    mbar_expect_tx(bar, tx_bytes);
#pragma unroll
    for (int p = 0; p < 3; p++) tma_load_4d(sbase + SMEM_SLOT + sl * SLOT_BYTES + p * PANEL_X, pmap_in, p * 64, c1, c2, c3, bar);
  };
  auto prefetch_l2 = [&](int j) {
    if (role == 0 && j < nj) {
      int c1, c2, c3; coords(j, c1, c2, c3);
#pragma unroll
      for (int p = 0; p < 3; p++) tma_prefetch_4d(pmap_in, p * 64, c1, c2, c3);
    }
  };

  if (tid >= NWG * 128) {
    asm volatile("setmaxnreg.dec.sync.aligned.u32 40;");
    if (tid == NWG * 128) {
      mbar_expect_tx(bar_w, 2 * WMAT_BYTES);
      bulk_load(sbase + SMEM_W0, &g_w[role * 2][0], WMAT_BYTES, bar_w);
      bulk_load(sbase + SMEM_W1, &g_w[role * 2 + 1][0], WMAT_BYTES, bar_w);
      for (int j = 0; j < NSLOT && j < nj; j++) issue_load(j);
      prefetch_l2(NSLOT); prefetch_l2(NSLOT + 1);
      for (int j = 0; j < nj; j++) {
        const int sl = j % NSLOT;
        mbar_wait(sbase + SMEM_MISC + 64 + 8 * sl, (j / NSLOT) & 1);
        int c1, c2, c3; coords(j, c1, c2, c3);
#pragma unroll
        for (int p = 0; p < 3; p++) tma_store_4d(pmap_out, sbase + SMEM_SLOT + sl * SLOT_BYTES + p * PANEL_X, p * 64, c1, c2, c3);
        bulk_commit();
        bulk_wait_read0();
        if (j + NSLOT < nj) issue_load(j + NSLOT);
        prefetch_l2(j + NSLOT + 2);
        if (role == 0) {
          bulk_wait0();
          asm volatile("fence.proxy.async.global;" ::: "memory");
          __threadfence();
          atomicAdd(&g_band_cnt[c3 / 7], 1u);
        }
      }
      bulk_wait0();
    }
    return;
  }
  asm volatile("setmaxnreg.inc.sync.aligned.u32 232;");
  mbar_wait(bar_w, 0);

  const int blk = lane >> 3;
  const int frow = 16 * w + (lane & 7) + ((blk & 1) << 3);
  const uint32_t fsw = frow & 7;
  const int fhi = blk >> 1;

  const uint64_t dW0 = make_desc(sbase + SMEM_W0, 16, 1024);
  const uint64_t dW1 = make_desc(sbase + SMEM_W1, 16, 1024);

  const float scale_l2e = 0.07216878364870322f * 1.4426950408889634f;

  for (int j = wg; j < nj; j += NWG) {
    const int sl = j % NSLOT;
    const uint32_t slot = sbase + SMEM_SLOT + sl * SLOT_BYTES;
    const uint32_t frowoff = slot + frow * 128;
    const uint64_t dX = make_desc(slot, 16, 1024);
    const uint64_t dXmn = make_desc(slot, PANEL_X, 1024);
    PH(0);
    mbar_wait(sbase + SMEM_MISC + 8 + 8 * sl, (j / NSLOT) & 1);
    PH(1);

    float acc[96];
    wgmma_fence();
#pragma unroll
    for (int kk = 0; kk < 12; kk++) {
      const uint32_t off = (kk >> 2) * PANEL_X + (kk & 3) * 32;
      const uint32_t offw = (kk >> 2) * PANEL_W + (kk & 3) * 32;
      wgmma_n192_ss(acc, dX + (off >> 4), dW0 + (offw >> 4), kk);
    }
    wgmma_commit();
    PH(2);
    const float rmine = row_rstd(slot, w, lane);
    PH(3);
    uint32_t fr[48], xf[48];

    if (role == 0) {
      wgmma_wait0(); acc_fence(acc);
      PH(4);
#pragma unroll
      for (int i = 0; i < 48; i++) fr[i] = pack_bf16(acc[2 * i], acc[2 * i + 1]);
#pragma unroll
      for (int kk = 0; kk < 12; kk++) ldsm_x4(frag_addr(frowoff, fsw, fhi, kk), xf[4 * kk], xf[4 * kk + 1], xf[4 * kk + 2], xf[4 * kk + 3]);
#pragma unroll
      for (int kk = 0; kk < 12; kk++) {
#pragma unroll
        for (int i = 0; i < 8; i++) acc[8 * kk + i] = 0.f;
        mma_16816(acc[8 * kk + 0], acc[8 * kk + 1], acc[8 * kk + 2], acc[8 * kk + 3], fr[4 * kk], fr[4 * kk + 1], fr[4 * kk + 2], fr[4 * kk + 3], xf[4 * kk], xf[4 * kk + 2]);
        mma_16816(acc[8 * kk + 4], acc[8 * kk + 5], acc[8 * kk + 6], acc[8 * kk + 7], fr[4 * kk], fr[4 * kk + 1], fr[4 * kk + 2], fr[4 * kk + 3], xf[4 * kk + 1], xf[4 * kk + 3]);
      }
      float d0[4], d1[4];
      {
        float t0 = 0.f, t1 = 0.f, t2 = 0.f, t3 = 0.f, u0 = 0.f, u1 = 0.f, u2 = 0.f, u3 = 0.f;
#pragma unroll
        for (int kk = 0; kk < 12; kk += 2) {
          t0 += acc[8 * kk + 0]; t1 += acc[8 * kk + 1]; t2 += acc[8 * kk + 6]; t3 += acc[8 * kk + 7];
          u0 += acc[8 * kk + 8]; u1 += acc[8 * kk + 9]; u2 += acc[8 * kk + 14]; u3 += acc[8 * kk + 15];
        }
        d0[0] = t0 + u0; d0[1] = t1 + u1; d1[2] = t2 + u2; d1[3] = t3 + u3;
      }
      const float rA = __shfl_sync(0xffffffffu, rmine, 2 * g);
      const float rB = __shfl_sync(0xffffffffu, rmine, 2 * g + 16);
      const float k0 = __shfl_sync(0xffffffffu, rmine, 4 * q);
      const float k1 = __shfl_sync(0xffffffffu, rmine, 4 * q + 2);
      const float k2 = __shfl_sync(0xffffffffu, rmine, 4 * q + 16);
      const float k3 = __shfl_sync(0xffffffffu, rmine, 4 * q + 18);
      const bool valid = (g >> 2) == (q >> 1);
      float sa0 = d0[0] * k0 * (rA * scale_l2e), sa1 = d0[1] * k1 * (rA * scale_l2e);
      float sb0 = d1[2] * k2 * (rB * scale_l2e), sb1 = d1[3] * k3 * (rB * scale_l2e);
      float ma = fmaxf(sa0, sa1), mb = fmaxf(sb0, sb1);
      ma = fmaxf(ma, __shfl_xor_sync(0xffffffffu, ma, 1));
      mb = fmaxf(mb, __shfl_xor_sync(0xffffffffu, mb, 1));
      const float ea0 = exp2f(sa0 - ma), ea1 = exp2f(sa1 - ma);
      const float eb0 = exp2f(sb0 - mb), eb1 = exp2f(sb1 - mb);
      float suma = ea0 + ea1, sumb = eb0 + eb1;
      suma += __shfl_xor_sync(0xffffffffu, suma, 1);
      sumb += __shfl_xor_sync(0xffffffffu, sumb, 1);
      const float ia = __fdividef(1.f, suma), ib = __fdividef(1.f, sumb);
      const uint32_t pa0 = valid ? pack_bf16(ea0 * ia * k0, ea1 * ia * k1) : 0u;
      const uint32_t pa3 = valid ? pack_bf16(eb0 * ib * k2, eb1 * ib * k3) : 0u;
      PH(5);
#pragma unroll
      for (int hh = 0; hh < 2; hh++) {
        uint32_t bt[24];
#pragma unroll
        for (int jj = 0; jj < 6; jj++) ldsm_x4_t(frag_addr(frowoff, fsw, fhi, hh * 6 + jj), bt[4 * jj], bt[4 * jj + 1], bt[4 * jj + 2], bt[4 * jj + 3]);
#pragma unroll
        for (int jj = 0; jj < 6; jj++) {
          const int o = 8 * (hh * 6 + jj);
          acc[o + 0] = 0.f; acc[o + 1] = 0.f; acc[o + 2] = 0.f; acc[o + 3] = 0.f;
          acc[o + 4] = 0.f; acc[o + 5] = 0.f; acc[o + 6] = 0.f; acc[o + 7] = 0.f;
          mma_16816(acc[o + 0], acc[o + 1], acc[o + 2], acc[o + 3], pa0, 0u, 0u, pa3, bt[4 * jj], bt[4 * jj + 1]);
          mma_16816(acc[o + 4], acc[o + 5], acc[o + 6], acc[o + 7], pa0, 0u, 0u, pa3, bt[4 * jj + 2], bt[4 * jj + 3]);
        }
      }
    } else {
      if ((lane & 1) == 0) rbuf[16 * w + (lane >> 1)] = rmine;
      wg_bar(1 + wg);
      wgmma_wait0(); acc_fence(acc);
      PH(4);
#pragma unroll
      for (int i = 0; i < 48; i++) fr[i] = pack_bf16(acc[2 * i], acc[2 * i + 1]);
      float s[28], s2[28];
      wgmma_fence();
#pragma unroll
      for (int kk = 0; kk < 12; kk += 2) {
        const uint32_t off = (kk >> 2) * PANEL_X + (kk & 3) * 32;
        wgmma_n56_rs(s, fr[4 * kk], fr[4 * kk + 1], fr[4 * kk + 2], fr[4 * kk + 3], dX + (off >> 4), kk);
        wgmma_n56_rs(s2, fr[4 * kk + 4], fr[4 * kk + 5], fr[4 * kk + 6], fr[4 * kk + 7], dX + ((off + 32) >> 4), kk);
      }
      wgmma_commit();
      float rj[14];
#pragma unroll
      for (int j = 0; j < 7; j++) {
        const float2 v = *reinterpret_cast<const float2*>(&rbuf[8 * j + 2 * q]);
        rj[2 * j] = v.x; rj[2 * j + 1] = v.y;
      }
      const float ri0 = rbuf[16 * w + g] * scale_l2e, ri1 = rbuf[16 * w + g + 8] * scale_l2e;
      wgmma_wait0(); acc_fence(s); acc_fence(s2);
#pragma unroll
      for (int i = 0; i < 28; i++) s[i] += s2[i];
      PH(5);
      float m0 = -INFINITY, m1 = -INFINITY;
#pragma unroll
      for (int j = 0; j < 7; j++) {
#pragma unroll
        for (int e = 0; e < 2; e++) {
          const bool ok = (j < 6) || (2 * q + e == 0);
          float v0 = s[4 * j + e] * rj[2 * j + e] * ri0;
          float v1 = s[4 * j + 2 + e] * rj[2 * j + e] * ri1;
          v0 = ok ? v0 : -INFINITY; v1 = ok ? v1 : -INFINITY;
          s[4 * j + e] = v0; s[4 * j + 2 + e] = v1;
          m0 = fmaxf(m0, v0); m1 = fmaxf(m1, v1);
        }
      }
      m0 = fmaxf(m0, __shfl_xor_sync(0xffffffffu, m0, 1)); m0 = fmaxf(m0, __shfl_xor_sync(0xffffffffu, m0, 2));
      m1 = fmaxf(m1, __shfl_xor_sync(0xffffffffu, m1, 1)); m1 = fmaxf(m1, __shfl_xor_sync(0xffffffffu, m1, 2));
      float sum0 = 0.f, sum1 = 0.f;
#pragma unroll
      for (int j = 0; j < 7; j++) {
#pragma unroll
        for (int e = 0; e < 2; e++) {
          const float e0 = exp2f(s[4 * j + e] - m0), e1 = exp2f(s[4 * j + 2 + e] - m1);
          s[4 * j + e] = e0; s[4 * j + 2 + e] = e1;
          sum0 += e0; sum1 += e1;
        }
      }
      sum0 += __shfl_xor_sync(0xffffffffu, sum0, 1); sum0 += __shfl_xor_sync(0xffffffffu, sum0, 2);
      sum1 += __shfl_xor_sync(0xffffffffu, sum1, 1); sum1 += __shfl_xor_sync(0xffffffffu, sum1, 2);
      const float i0 = __fdividef(1.f, sum0), i1 = __fdividef(1.f, sum1);
      uint32_t pa[16];
#pragma unroll
      for (int j = 0; j < 7; j++) {
        pa[(j >> 1) * 4 + (j & 1) * 2 + 0] = pack_bf16(s[4 * j] * i0 * rj[2 * j], s[4 * j + 1] * i0 * rj[2 * j + 1]);
        pa[(j >> 1) * 4 + (j & 1) * 2 + 1] = pack_bf16(s[4 * j + 2] * i1 * rj[2 * j], s[4 * j + 3] * i1 * rj[2 * j + 1]);
      }
      pa[14] = 0u; pa[15] = 0u;
      PH(6);
      wgmma_fence();
#pragma unroll
      for (int kk = 0; kk < 4; kk++)
        wgmma_n192_rs_tb(acc, pa[4 * kk], pa[4 * kk + 1], pa[4 * kk + 2], pa[4 * kk + 3], dXmn + ((kk * 2048) >> 4), kk);
      wgmma_commit();
      wgmma_wait0(); acc_fence(acc);
    }

    PH(7);
#pragma unroll
    for (int i = 0; i < 48; i++) fr[i] = pack_bf16(acc[2 * i], acc[2 * i + 1]);
    wgmma_fence();
#pragma unroll
    for (int kk = 0; kk < 12; kk++) {
      const uint32_t offw = (kk >> 2) * PANEL_W + (kk & 3) * 32;
      wgmma_n192_rs(acc, fr[4 * kk], fr[4 * kk + 1], fr[4 * kk + 2], fr[4 * kk + 3], dW1 + (offw >> 4), kk);
    }
    wgmma_commit();
    if (role != 0) {
#pragma unroll
      for (int kk = 0; kk < 12; kk++) ldsm_x4(frag_addr(frowoff, fsw, fhi, kk), xf[4 * kk], xf[4 * kk + 1], xf[4 * kk + 2], xf[4 * kk + 3]);
    }
    wgmma_wait0(); acc_fence(acc);
    PH(8);
    wg_bar(1 + wg);
    PH(9);
#pragma unroll
    for (int kk = 0; kk < 12; kk++) {
      const uint32_t o0 = add_bf16x2(xf[4 * kk + 0], pack_bf16(acc[8 * kk + 0], acc[8 * kk + 1]));
      const uint32_t o1 = add_bf16x2(xf[4 * kk + 1], pack_bf16(acc[8 * kk + 2], acc[8 * kk + 3]));
      const uint32_t o2 = add_bf16x2(xf[4 * kk + 2], pack_bf16(acc[8 * kk + 4], acc[8 * kk + 5]));
      const uint32_t o3 = add_bf16x2(xf[4 * kk + 3], pack_bf16(acc[8 * kk + 6], acc[8 * kk + 7]));
      stsm_x4(frag_addr(frowoff, fsw, fhi, kk), o0, o1, o2, o3);
    }
    PH(10);
    fence_proxy_async();
    mbar_arrive(sbase + SMEM_MISC + 64 + 8 * sl);
    PH(11);
  }
}

typedef CUresult (*EncodeTiledFn)(CUtensorMap*, CUtensorMapDataType, cuuint32_t, void*, const cuuint64_t*, const cuuint64_t*,
                                  const cuuint32_t*, const cuuint32_t*, CUtensorMapInterleave, CUtensorMapSwizzle,
                                  CUtensorMapL2promotion, CUtensorMapFloatOOBfill);

bool make_map(EncodeTiledFn fn, CUtensorMap* m, void* base, bool pixel_major) {
  cuuint64_t dims[4]; cuuint64_t strides[3]; cuuint32_t box[4]; cuuint32_t es[4] = {1, 1, 1, 1};
  const cuuint64_t sC = (cuuint64_t)CH * 2, sW = sC * WW, sT = sW * HH;
  if (pixel_major) {
    dims[0] = CH; dims[1] = TT; dims[2] = WW; dims[3] = HH;
    strides[0] = sT; strides[1] = sC; strides[2] = sW;
    box[0] = 64; box[1] = 4; box[2] = 16; box[3] = 1;
  } else {
    dims[0] = CH; dims[1] = WW; dims[2] = HH; dims[3] = TT;
    strides[0] = sC; strides[1] = sW; strides[2] = sT;
    box[0] = 64; box[1] = 7; box[2] = 7; box[3] = 1;
  }
  return fn(m, CU_TENSOR_MAP_DATA_TYPE_BFLOAT16, 4, base, dims, strides, box, es, CU_TENSOR_MAP_INTERLEAVE_NONE,
            CU_TENSOR_MAP_SWIZZLE_128B, CU_TENSOR_MAP_L2_PROMOTION_L2_256B, CU_TENSOR_MAP_FLOAT_OOB_FILL_NONE) == CUDA_SUCCESS;
}

}

extern "C" void kernel_launch(void* const* d_in, const int* in_sizes, int n_in, void* d_out, int out_size) {
  const __nv_bfloat16* x = (const __nv_bfloat16*)d_in[0];
  const __nv_bfloat16* wqkv_t = (const __nv_bfloat16*)d_in[1];
  const __nv_bfloat16* wo_t = (const __nv_bfloat16*)d_in[2];
  const __nv_bfloat16* wqkv_s = (const __nv_bfloat16*)d_in[3];
  const __nv_bfloat16* wo_s = (const __nv_bfloat16*)d_in[4];

  static bool init = false;
  static CUtensorMap mA_in, mA_out, mB_in, mB_out;
  static void* last_x = nullptr; static void* last_out = nullptr;
  static int nsm = 132;
  if (!init || last_x != d_in[0] || last_out != d_out) {
    void* fnp = nullptr; cudaDriverEntryPointQueryResult qr;
    cudaGetDriverEntryPoint("cuTensorMapEncodeTiled", &fnp, cudaEnableDefault, &qr);
    EncodeTiledFn fn = (EncodeTiledFn)fnp;
    void* x1p = nullptr; cudaGetSymbolAddress(&x1p, g_x1);
    make_map(fn, &mA_in, (void*)x, true);
    make_map(fn, &mA_out, x1p, true);
    make_map(fn, &mB_in, x1p, false);
    make_map(fn, &mB_out, d_out, false);
    cudaFuncSetAttribute(fold_weights_kernel, cudaFuncAttributeMaxDynamicSharedMemorySize, FW_SMEM);
    cudaFuncSetAttribute(swin_main_kernel, cudaFuncAttributeMaxDynamicSharedMemorySize, SMEM_TOTAL);
    cudaDeviceGetAttribute(&nsm, cudaDevAttrMultiProcessorCount, 0);
    init = true; last_x = d_in[0]; last_out = d_out;
  }
  fold_weights_kernel<<<dim3(12, 4), 384, FW_SMEM>>>(wqkv_t, wo_t, wqkv_s, wo_s);
  swin_main_kernel<<<nsm, NWG * 128 + 128, SMEM_TOTAL>>>(mA_in, mA_out, mB_in, mB_out, NUM_A);
}
```

```cpp
#include <cuda_runtime.h>
#include <cuda_bf16.h>
#include <cuda.h>
#include <stdint.h>

namespace {

constexpr int CH = 192;
constexpr int TT = 4, HH = 224, WW = 224;
constexpr int NTOK = TT * HH * WW;
constexpr int PANEL_X = 64 * 128;
constexpr int SLOT_BYTES = 3 * PANEL_X;
constexpr int PANEL_W = 192 * 128;
constexpr int WMAT_BYTES = 3 * PANEL_W;
constexpr int NWG = 2;
constexpr int NSLOT = 3;
constexpr int SMEM_W0 = 0;
constexpr int SMEM_W1 = WMAT_BYTES;
constexpr int SMEM_SLOT = 2 * WMAT_BYTES;
constexpr int SMEM_MISC = SMEM_SLOT + NSLOT * SLOT_BYTES;
constexpr int SMEM_RBUF = SMEM_MISC + 128;
constexpr int SMEM_TOTAL = SMEM_RBUF + NWG * 64 * 4;

constexpr int NTILE_A = HH * (WW / 16);
constexpr int NUNIT_B = 32 * 32 * 4;
#define NUM_A 56

__device__ __nv_bfloat16 g_x1[(size_t)NTOK * CH];
__device__ unsigned int g_band_cnt[32];
__device__ __align__(1024) __nv_bfloat16 g_w[4][CH * CH];

#define PH(i) do {} while (0)
__device__ __forceinline__ uint32_t smem_u32(const void* p) { return (uint32_t)__cvta_generic_to_shared(p); }

__device__ __forceinline__ void mbar_init(uint32_t bar, uint32_t count) {
  asm volatile("mbarrier.init.shared::cta.b64 [%0], %1;" :: "r"(bar), "r"(count));
}
__device__ __forceinline__ void mbar_expect_tx(uint32_t bar, uint32_t bytes) {
  asm volatile("mbarrier.arrive.expect_tx.shared::cta.b64 _, [%0], %1;" :: "r"(bar), "r"(bytes) : "memory");
}
__device__ __forceinline__ void mbar_arrive(uint32_t bar) {
  asm volatile("mbarrier.arrive.shared::cta.b64 _, [%0];" :: "r"(bar) : "memory");
}
__device__ __forceinline__ void mbar_wait(uint32_t bar, uint32_t parity) {
  asm volatile(
    "{\n.reg .pred p;\n"
    "WAIT_%=:\n"
    "mbarrier.try_wait.parity.shared::cta.b64 p, [%0], %1;\n"
    "@p bra DONE_%=;\n"
    "bra WAIT_%=;\n"
    "DONE_%=:\n}\n" :: "r"(bar), "r"(parity) : "memory");
}
__device__ __forceinline__ void tma_load_4d(uint32_t dst, const CUtensorMap* map, int c0, int c1, int c2, int c3, uint32_t bar) {
  asm volatile("cp.async.bulk.tensor.4d.shared::cluster.global.tile.mbarrier::complete_tx::bytes [%0], [%1, {%2, %3, %4, %5}], [%6];"
    :: "r"(dst), "l"(map), "r"(c0), "r"(c1), "r"(c2), "r"(c3), "r"(bar) : "memory");
}
__device__ __forceinline__ void tma_prefetch_4d(const CUtensorMap* map, int c0, int c1, int c2, int c3) {
  asm volatile("cp.async.bulk.prefetch.tensor.4d.L2.global.tile [%0, {%1, %2, %3, %4}];"
    :: "l"(map), "r"(c0), "r"(c1), "r"(c2), "r"(c3) : "memory");
}
__device__ __forceinline__ void tma_store_4d(const CUtensorMap* map, uint32_t src, int c0, int c1, int c2, int c3) {
  asm volatile("cp.async.bulk.tensor.4d.global.shared::cta.tile.bulk_group [%0, {%1, %2, %3, %4}], [%5];"
    :: "l"(map), "r"(c0), "r"(c1), "r"(c2), "r"(c3), "r"(src) : "memory");
}
__device__ __forceinline__ void bulk_load(uint32_t dst, const void* src, uint32_t bytes, uint32_t bar) {
  asm volatile("cp.async.bulk.shared::cluster.global.mbarrier::complete_tx::bytes [%0], [%1], %2, [%3];"
    :: "r"(dst), "l"(src), "r"(bytes), "r"(bar) : "memory");
}
__device__ __forceinline__ void bulk_commit() { asm volatile("cp.async.bulk.commit_group;" ::: "memory"); }
__device__ __forceinline__ void bulk_wait_read0() { asm volatile("cp.async.bulk.wait_group.read 0;" ::: "memory"); }
__device__ __forceinline__ void bulk_wait0() { asm volatile("cp.async.bulk.wait_group 0;" ::: "memory"); }
__device__ __forceinline__ void fence_proxy_async() { asm volatile("fence.proxy.async.shared::cta;" ::: "memory"); }
__device__ __forceinline__ void wg_bar(int id) { asm volatile("bar.sync %0, 128;" :: "r"(id) : "memory"); }
__device__ __forceinline__ void turn_wait(int wg) { asm volatile("bar.sync %0, 256;" :: "r"(4 + wg) : "memory"); }
__device__ __forceinline__ void turn_pass(int wg) { asm volatile("bar.arrive %0, 256;" :: "r"(4 + (wg ^ 1)) : "memory"); }
__device__ __forceinline__ void wgmma_fence() { asm volatile("wgmma.fence.sync.aligned;" ::: "memory"); }
__device__ __forceinline__ void wgmma_commit() { asm volatile("wgmma.commit_group.sync.aligned;" ::: "memory"); }
__device__ __forceinline__ void wgmma_wait0() { asm volatile("wgmma.wait_group.sync.aligned 0;" ::: "memory"); }

__device__ __forceinline__ uint64_t make_desc(uint32_t saddr, uint32_t lbo, uint32_t sbo) {
  return (uint64_t)((saddr & 0x3FFFF) >> 4) | ((uint64_t)((lbo & 0x3FFFF) >> 4) << 16) |
         ((uint64_t)((sbo & 0x3FFFF) >> 4) << 32) | ((uint64_t)1 << 62);
}
__device__ __forceinline__ uint32_t pack_bf16(float lo, float hi) {
  uint32_t r; asm("cvt.rn.bf16x2.f32 %0, %1, %2;" : "=r"(r) : "f"(hi), "f"(lo)); return r;
}
__device__ __forceinline__ uint32_t add_bf16x2(uint32_t a, uint32_t b) {
  uint32_t r; asm("add.rn.bf16x2 %0, %1, %2;" : "=r"(r) : "r"(a), "r"(b)); return r;
}
__device__ __forceinline__ float bf_lo(uint32_t u) { return __uint_as_float(u << 16); }
__device__ __forceinline__ float bf_hi(uint32_t u) { return __uint_as_float(u & 0xffff0000u); }
__device__ __forceinline__ void ldsm_x4(uint32_t addr, uint32_t& r0, uint32_t& r1, uint32_t& r2, uint32_t& r3) {
  asm volatile("ldmatrix.sync.aligned.m8n8.x4.shared.b16 {%0,%1,%2,%3}, [%4];"
    : "=r"(r0), "=r"(r1), "=r"(r2), "=r"(r3) : "r"(addr) : "memory");
}
__device__ __forceinline__ void ldsm_x4_t(uint32_t addr, uint32_t& r0, uint32_t& r1, uint32_t& r2, uint32_t& r3) {
  asm volatile("ldmatrix.sync.aligned.m8n8.x4.trans.shared.b16 {%0,%1,%2,%3}, [%4];"
    : "=r"(r0), "=r"(r1), "=r"(r2), "=r"(r3) : "r"(addr) : "memory");
}
__device__ __forceinline__ void stsm_x4(uint32_t addr, uint32_t r0, uint32_t r1, uint32_t r2, uint32_t r3) {
  asm volatile("stmatrix.sync.aligned.m8n8.x4.shared.b16 [%0], {%1,%2,%3,%4};"
    :: "r"(addr), "r"(r0), "r"(r1), "r"(r2), "r"(r3) : "memory");
}
__device__ __forceinline__ void mma_16816(float& d0, float& d1, float& d2, float& d3,
                                          uint32_t a0, uint32_t a1, uint32_t a2, uint32_t a3, uint32_t b0, uint32_t b1) {
  asm volatile("mma.sync.aligned.m16n8k16.row.col.f32.bf16.bf16.f32 {%0,%1,%2,%3}, {%4,%5,%6,%7}, {%8,%9}, {%0,%1,%2,%3};"
    : "+f"(d0), "+f"(d1), "+f"(d2), "+f"(d3) : "r"(a0), "r"(a1), "r"(a2), "r"(a3), "r"(b0), "r"(b1));
}
__device__ __forceinline__ uint4 lds128(uint32_t addr) {
  uint4 v; asm volatile("ld.shared.v4.u32 {%0,%1,%2,%3}, [%4];" : "=r"(v.x), "=r"(v.y), "=r"(v.z), "=r"(v.w) : "r"(addr) : "memory");
  return v;
}

__device__ __forceinline__ void wgmma_n192_ss(float (&d)[96], uint64_t da, uint64_t db, int scale_d) {
  asm volatile("{\n.reg .pred p;\nsetp.ne.b32 p, %98, 0;\n"
    "wgmma.mma_async.sync.aligned.m64n192k16.f32.bf16.bf16 {%0, %1, %2, %3, %4, %5, %6, %7, %8, %9, %10, %11, %12, %13, %14, %15, %16, %17, %18, %19, %20, %21, %22, %23, %24, %25, %26, %27, %28, %29, %30, %31, %32, %33, %34, %35, %36, %37, %38, %39, %40, %41, %42, %43, %44, %45, %46, %47, %48, %49, %50, %51, %52, %53, %54, %55, %56, %57, %58, %59, %60, %61, %62, %63, %64, %65, %66, %67, %68, %69, %70, %71, %72, %73, %74, %75, %76, %77, %78, %79, %80, %81, %82, %83, %84, %85, %86, %87, %88, %89, %90, %91, %92, %93, %94, %95}, %96, %97, p, 1, 1, 0, 0;\n}\n"
    : "+f"(d[0]), "+f"(d[1]), "+f"(d[2]), "+f"(d[3]), "+f"(d[4]), "+f"(d[5]), "+f"(d[6]), "+f"(d[7]), "+f"(d[8]), "+f"(d[9]), "+f"(d[10]), "+f"(d[11]), "+f"(d[12]), "+f"(d[13]), "+f"(d[14]), "+f"(d[15]), "+f"(d[16]), "+f"(d[17]), "+f"(d[18]), "+f"(d[19]), "+f"(d[20]), "+f"(d[21]), "+f"(d[22]), "+f"(d[23]), "+f"(d[24]), "+f"(d[25]), "+f"(d[26]), "+f"(d[27]), "+f"(d[28]), "+f"(d[29]), "+f"(d[30]), "+f"(d[31]), "+f"(d[32]), "+f"(d[33]), "+f"(d[34]), "+f"(d[35]), "+f"(d[36]), "+f"(d[37]), "+f"(d[38]), "+f"(d[39]), "+f"(d[40]), "+f"(d[41]), "+f"(d[42]), "+f"(d[43]), "+f"(d[44]), "+f"(d[45]), "+f"(d[46]), "+f"(d[47]), "+f"(d[48]), "+f"(d[49]), "+f"(d[50]), "+f"(d[51]), "+f"(d[52]), "+f"(d[53]), "+f"(d[54]), "+f"(d[55]), "+f"(d[56]), "+f"(d[57]), "+f"(d[58]), "+f"(d[59]), "+f"(d[60]), "+f"(d[61]), "+f"(d[62]), "+f"(d[63]), "+f"(d[64]), "+f"(d[65]), "+f"(d[66]), "+f"(d[67]), "+f"(d[68]), "+f"(d[69]), "+f"(d[70]), "+f"(d[71]), "+f"(d[72]), "+f"(d[73]), "+f"(d[74]), "+f"(d[75]), "+f"(d[76]), "+f"(d[77]), "+f"(d[78]), "+f"(d[79]), "+f"(d[80]), "+f"(d[81]), "+f"(d[82]), "+f"(d[83]), "+f"(d[84]), "+f"(d[85]), "+f"(d[86]), "+f"(d[87]), "+f"(d[88]), "+f"(d[89]), "+f"(d[90]), "+f"(d[91]), "+f"(d[92]), "+f"(d[93]), "+f"(d[94]), "+f"(d[95])
    : "l"(da), "l"(db), "r"(scale_d));
}

__device__ __forceinline__ void wgmma_n192_rs(float (&d)[96], uint32_t a0, uint32_t a1, uint32_t a2, uint32_t a3, uint64_t db, int scale_d) {
  asm volatile("{\n.reg .pred p;\nsetp.ne.b32 p, %101, 0;\n"
    "wgmma.mma_async.sync.aligned.m64n192k16.f32.bf16.bf16 {%0, %1, %2, %3, %4, %5, %6, %7, %8, %9, %10, %11, %12, %13, %14, %15, %16, %17, %18, %19, %20, %21, %22, %23, %24, %25, %26, %27, %28, %29, %30, %31, %32, %33, %34, %35, %36, %37, %38, %39, %40, %41, %42, %43, %44, %45, %46, %47, %48, %49, %50, %51, %52, %53, %54, %55, %56, %57, %58, %59, %60, %61, %62, %63, %64, %65, %66, %67, %68, %69, %70, %71, %72, %73, %74, %75, %76, %77, %78, %79, %80, %81, %82, %83, %84, %85, %86, %87, %88, %89, %90, %91, %92, %93, %94, %95}, {%96, %97, %98, %99}, %100, p, 1, 1, 0;\n}\n"
    : "+f"(d[0]), "+f"(d[1]), "+f"(d[2]), "+f"(d[3]), "+f"(d[4]), "+f"(d[5]), "+f"(d[6]), "+f"(d[7]), "+f"(d[8]), "+f"(d[9]), "+f"(d[10]), "+f"(d[11]), "+f"(d[12]), "+f"(d[13]), "+f"(d[14]), "+f"(d[15]), "+f"(d[16]), "+f"(d[17]), "+f"(d[18]), "+f"(d[19]), "+f"(d[20]), "+f"(d[21]), "+f"(d[22]), "+f"(d[23]), "+f"(d[24]), "+f"(d[25]), "+f"(d[26]), "+f"(d[27]), "+f"(d[28]), "+f"(d[29]), "+f"(d[30]), "+f"(d[31]), "+f"(d[32]), "+f"(d[33]), "+f"(d[34]), "+f"(d[35]), "+f"(d[36]), "+f"(d[37]), "+f"(d[38]), "+f"(d[39]), "+f"(d[40]), "+f"(d[41]), "+f"(d[42]), "+f"(d[43]), "+f"(d[44]), "+f"(d[45]), "+f"(d[46]), "+f"(d[47]), "+f"(d[48]), "+f"(d[49]), "+f"(d[50]), "+f"(d[51]), "+f"(d[52]), "+f"(d[53]), "+f"(d[54]), "+f"(d[55]), "+f"(d[56]), "+f"(d[57]), "+f"(d[58]), "+f"(d[59]), "+f"(d[60]), "+f"(d[61]), "+f"(d[62]), "+f"(d[63]), "+f"(d[64]), "+f"(d[65]), "+f"(d[66]), "+f"(d[67]), "+f"(d[68]), "+f"(d[69]), "+f"(d[70]), "+f"(d[71]), "+f"(d[72]), "+f"(d[73]), "+f"(d[74]), "+f"(d[75]), "+f"(d[76]), "+f"(d[77]), "+f"(d[78]), "+f"(d[79]), "+f"(d[80]), "+f"(d[81]), "+f"(d[82]), "+f"(d[83]), "+f"(d[84]), "+f"(d[85]), "+f"(d[86]), "+f"(d[87]), "+f"(d[88]), "+f"(d[89]), "+f"(d[90]), "+f"(d[91]), "+f"(d[92]), "+f"(d[93]), "+f"(d[94]), "+f"(d[95])
    : "r"(a0), "r"(a1), "r"(a2), "r"(a3), "l"(db), "r"(scale_d));
}

__device__ __forceinline__ void wgmma_n192_rs_tb(float (&d)[96], uint32_t a0, uint32_t a1, uint32_t a2, uint32_t a3, uint64_t db, int scale_d) {
  asm volatile("{\n.reg .pred p;\nsetp.ne.b32 p, %101, 0;\n"
    "wgmma.mma_async.sync.aligned.m64n192k16.f32.bf16.bf16 {%0, %1, %2, %3, %4, %5, %6, %7, %8, %9, %10, %11, %12, %13, %14, %15, %16, %17, %18, %19, %20, %21, %22, %23, %24, %25, %26, %27, %28, %29, %30, %31, %32, %33, %34, %35, %36, %37, %38, %39, %40, %41, %42, %43, %44, %45, %46, %47, %48, %49, %50, %51, %52, %53, %54, %55, %56, %57, %58, %59, %60, %61, %62, %63, %64, %65, %66, %67, %68, %69, %70, %71, %72, %73, %74, %75, %76, %77, %78, %79, %80, %81, %82, %83, %84, %85, %86, %87, %88, %89, %90, %91, %92, %93, %94, %95}, {%96, %97, %98, %99}, %100, p, 1, 1, 1;\n}\n"
    : "+f"(d[0]), "+f"(d[1]), "+f"(d[2]), "+f"(d[3]), "+f"(d[4]), "+f"(d[5]), "+f"(d[6]), "+f"(d[7]), "+f"(d[8]), "+f"(d[9]), "+f"(d[10]), "+f"(d[11]), "+f"(d[12]), "+f"(d[13]), "+f"(d[14]), "+f"(d[15]), "+f"(d[16]), "+f"(d[17]), "+f"(d[18]), "+f"(d[19]), "+f"(d[20]), "+f"(d[21]), "+f"(d[22]), "+f"(d[23]), "+f"(d[24]), "+f"(d[25]), "+f"(d[26]), "+f"(d[27]), "+f"(d[28]), "+f"(d[29]), "+f"(d[30]), "+f"(d[31]), "+f"(d[32]), "+f"(d[33]), "+f"(d[34]), "+f"(d[35]), "+f"(d[36]), "+f"(d[37]), "+f"(d[38]), "+f"(d[39]), "+f"(d[40]), "+f"(d[41]), "+f"(d[42]), "+f"(d[43]), "+f"(d[44]), "+f"(d[45]), "+f"(d[46]), "+f"(d[47]), "+f"(d[48]), "+f"(d[49]), "+f"(d[50]), "+f"(d[51]), "+f"(d[52]), "+f"(d[53]), "+f"(d[54]), "+f"(d[55]), "+f"(d[56]), "+f"(d[57]), "+f"(d[58]), "+f"(d[59]), "+f"(d[60]), "+f"(d[61]), "+f"(d[62]), "+f"(d[63]), "+f"(d[64]), "+f"(d[65]), "+f"(d[66]), "+f"(d[67]), "+f"(d[68]), "+f"(d[69]), "+f"(d[70]), "+f"(d[71]), "+f"(d[72]), "+f"(d[73]), "+f"(d[74]), "+f"(d[75]), "+f"(d[76]), "+f"(d[77]), "+f"(d[78]), "+f"(d[79]), "+f"(d[80]), "+f"(d[81]), "+f"(d[82]), "+f"(d[83]), "+f"(d[84]), "+f"(d[85]), "+f"(d[86]), "+f"(d[87]), "+f"(d[88]), "+f"(d[89]), "+f"(d[90]), "+f"(d[91]), "+f"(d[92]), "+f"(d[93]), "+f"(d[94]), "+f"(d[95])
    : "r"(a0), "r"(a1), "r"(a2), "r"(a3), "l"(db), "r"(scale_d));
}

__device__ __forceinline__ void wgmma_n56_rs(float (&d)[28], uint32_t a0, uint32_t a1, uint32_t a2, uint32_t a3, uint64_t db, int scale_d) {
  asm volatile("{\n.reg .pred p;\nsetp.ne.b32 p, %33, 0;\n"
    "wgmma.mma_async.sync.aligned.m64n56k16.f32.bf16.bf16 {%0, %1, %2, %3, %4, %5, %6, %7, %8, %9, %10, %11, %12, %13, %14, %15, %16, %17, %18, %19, %20, %21, %22, %23, %24, %25, %26, %27}, {%28, %29, %30, %31}, %32, p, 1, 1, 0;\n}\n"
    : "+f"(d[0]), "+f"(d[1]), "+f"(d[2]), "+f"(d[3]), "+f"(d[4]), "+f"(d[5]), "+f"(d[6]), "+f"(d[7]), "+f"(d[8]), "+f"(d[9]), "+f"(d[10]), "+f"(d[11]), "+f"(d[12]), "+f"(d[13]), "+f"(d[14]), "+f"(d[15]), "+f"(d[16]), "+f"(d[17]), "+f"(d[18]), "+f"(d[19]), "+f"(d[20]), "+f"(d[21]), "+f"(d[22]), "+f"(d[23]), "+f"(d[24]), "+f"(d[25]), "+f"(d[26]), "+f"(d[27])
    : "r"(a0), "r"(a1), "r"(a2), "r"(a3), "l"(db), "r"(scale_d));
}

__device__ __forceinline__ void wgmma_n96_rs(float (&d)[48], uint32_t a0, uint32_t a1, uint32_t a2, uint32_t a3, uint64_t db, int scale_d) {
  asm volatile("{\n.reg .pred p;\nsetp.ne.b32 p, %53, 0;\n"
    "wgmma.mma_async.sync.aligned.m64n96k16.f32.bf16.bf16 {%0, %1, %2, %3, %4, %5, %6, %7, %8, %9, %10, %11, %12, %13, %14, %15, %16, %17, %18, %19, %20, %21, %22, %23, %24, %25, %26, %27, %28, %29, %30, %31, %32, %33, %34, %35, %36, %37, %38, %39, %40, %41, %42, %43, %44, %45, %46, %47}, {%48, %49, %50, %51}, %52, p, 1, 1, 0;\n}\n"
    : "+f"(d[0]), "+f"(d[1]), "+f"(d[2]), "+f"(d[3]), "+f"(d[4]), "+f"(d[5]), "+f"(d[6]), "+f"(d[7]), "+f"(d[8]), "+f"(d[9]), "+f"(d[10]), "+f"(d[11]), "+f"(d[12]), "+f"(d[13]), "+f"(d[14]), "+f"(d[15]), "+f"(d[16]), "+f"(d[17]), "+f"(d[18]), "+f"(d[19]), "+f"(d[20]), "+f"(d[21]), "+f"(d[22]), "+f"(d[23]), "+f"(d[24]), "+f"(d[25]), "+f"(d[26]), "+f"(d[27]), "+f"(d[28]), "+f"(d[29]), "+f"(d[30]), "+f"(d[31]), "+f"(d[32]), "+f"(d[33]), "+f"(d[34]), "+f"(d[35]), "+f"(d[36]), "+f"(d[37]), "+f"(d[38]), "+f"(d[39]), "+f"(d[40]), "+f"(d[41]), "+f"(d[42]), "+f"(d[43]), "+f"(d[44]), "+f"(d[45]), "+f"(d[46]), "+f"(d[47])
    : "r"(a0), "r"(a1), "r"(a2), "r"(a3), "l"(db), "r"(scale_d));
}

__device__ __forceinline__ void acc_fence(float (&d)[96]) {
  asm volatile("" : "+f"(d[0]), "+f"(d[1]), "+f"(d[2]), "+f"(d[3]), "+f"(d[4]), "+f"(d[5]), "+f"(d[6]), "+f"(d[7]), "+f"(d[8]), "+f"(d[9]), "+f"(d[10]), "+f"(d[11]), "+f"(d[12]), "+f"(d[13]), "+f"(d[14]), "+f"(d[15]), "+f"(d[16]), "+f"(d[17]), "+f"(d[18]), "+f"(d[19]), "+f"(d[20]), "+f"(d[21]), "+f"(d[22]), "+f"(d[23]), "+f"(d[24]), "+f"(d[25]), "+f"(d[26]), "+f"(d[27]), "+f"(d[28]), "+f"(d[29]), "+f"(d[30]), "+f"(d[31]), "+f"(d[32]), "+f"(d[33]), "+f"(d[34]), "+f"(d[35]), "+f"(d[36]), "+f"(d[37]), "+f"(d[38]), "+f"(d[39]), "+f"(d[40]), "+f"(d[41]), "+f"(d[42]), "+f"(d[43]), "+f"(d[44]), "+f"(d[45]), "+f"(d[46]), "+f"(d[47]), "+f"(d[48]), "+f"(d[49]), "+f"(d[50]), "+f"(d[51]), "+f"(d[52]), "+f"(d[53]), "+f"(d[54]), "+f"(d[55]), "+f"(d[56]), "+f"(d[57]), "+f"(d[58]), "+f"(d[59]), "+f"(d[60]), "+f"(d[61]), "+f"(d[62]), "+f"(d[63]), "+f"(d[64]), "+f"(d[65]), "+f"(d[66]), "+f"(d[67]), "+f"(d[68]), "+f"(d[69]), "+f"(d[70]), "+f"(d[71]), "+f"(d[72]), "+f"(d[73]), "+f"(d[74]), "+f"(d[75]), "+f"(d[76]), "+f"(d[77]), "+f"(d[78]), "+f"(d[79]), "+f"(d[80]), "+f"(d[81]), "+f"(d[82]), "+f"(d[83]), "+f"(d[84]), "+f"(d[85]), "+f"(d[86]), "+f"(d[87]), "+f"(d[88]), "+f"(d[89]), "+f"(d[90]), "+f"(d[91]), "+f"(d[92]), "+f"(d[93]), "+f"(d[94]), "+f"(d[95]) :: "memory");
}

__device__ __forceinline__ void acc_fence(float (&d)[28]) {
  asm volatile("" : "+f"(d[0]), "+f"(d[1]), "+f"(d[2]), "+f"(d[3]), "+f"(d[4]), "+f"(d[5]), "+f"(d[6]), "+f"(d[7]), "+f"(d[8]), "+f"(d[9]), "+f"(d[10]), "+f"(d[11]), "+f"(d[12]), "+f"(d[13]), "+f"(d[14]), "+f"(d[15]), "+f"(d[16]), "+f"(d[17]), "+f"(d[18]), "+f"(d[19]), "+f"(d[20]), "+f"(d[21]), "+f"(d[22]), "+f"(d[23]), "+f"(d[24]), "+f"(d[25]), "+f"(d[26]), "+f"(d[27]) :: "memory");
}

__device__ __forceinline__ void acc_fence(float (&d)[48]) {
  asm volatile("" : "+f"(d[0]), "+f"(d[1]), "+f"(d[2]), "+f"(d[3]), "+f"(d[4]), "+f"(d[5]), "+f"(d[6]), "+f"(d[7]), "+f"(d[8]), "+f"(d[9]), "+f"(d[10]), "+f"(d[11]), "+f"(d[12]), "+f"(d[13]), "+f"(d[14]), "+f"(d[15]), "+f"(d[16]), "+f"(d[17]), "+f"(d[18]), "+f"(d[19]), "+f"(d[20]), "+f"(d[21]), "+f"(d[22]), "+f"(d[23]), "+f"(d[24]), "+f"(d[25]), "+f"(d[26]), "+f"(d[27]), "+f"(d[28]), "+f"(d[29]), "+f"(d[30]), "+f"(d[31]), "+f"(d[32]), "+f"(d[33]), "+f"(d[34]), "+f"(d[35]), "+f"(d[36]), "+f"(d[37]), "+f"(d[38]), "+f"(d[39]), "+f"(d[40]), "+f"(d[41]), "+f"(d[42]), "+f"(d[43]), "+f"(d[44]), "+f"(d[45]), "+f"(d[46]), "+f"(d[47]) :: "memory");
}

constexpr int FW_LD = 200;
__global__ void __launch_bounds__(384) fold_weights_kernel(const __nv_bfloat16* __restrict__ wqkv_t, const __nv_bfloat16* __restrict__ wo_t,
                                    const __nv_bfloat16* __restrict__ wqkv_s, const __nv_bfloat16* __restrict__ wo_s) {
  extern __shared__ __align__(16) uint8_t fsm[];
  __nv_bfloat16* As = reinterpret_cast<__nv_bfloat16*>(fsm);
  float* part = reinterpret_cast<float*>(fsm + CH * FW_LD * 2);
  float* part2 = part + 16 * CH;
  float* cm = part2 + 16 * CH;
  float* Bs = cm + CH;
  const int mat = blockIdx.y, n0 = blockIdx.x * 16, tid = threadIdx.x;
  if (mat == 0 && blockIdx.x == 0 && tid < 32) g_band_cnt[tid] = 0u;
  const __nv_bfloat16* wqkv = (mat < 2) ? wqkv_t : wqkv_s;
  const __nv_bfloat16* wo = (mat < 2) ? wo_t : wo_s;
  const bool isM = (mat & 1) == 0;
  const int offA = isM ? 0 : 2 * CH;
  const int cg = tid % 24, rg = tid / 24;
  {
    uint4 va[12], vb[12];
#pragma unroll
    for (int i = 0; i < 12; i++) va[i] = *reinterpret_cast<const uint4*>(wqkv + (rg * 12 + i) * 3 * CH + offA + cg * 8);
    if (isM) {
#pragma unroll
      for (int i = 0; i < 12; i++) vb[i] = *reinterpret_cast<const uint4*>(wqkv + (rg * 12 + i) * 3 * CH + CH + cg * 8);
    } else {
#pragma unroll
      for (int i = 0; i < 12; i++) vb[i] = make_uint4(0, 0, 0, 0);
    }
    float sa[8] = {0.f, 0.f, 0.f, 0.f, 0.f, 0.f, 0.f, 0.f}, sb[8] = {0.f, 0.f, 0.f, 0.f, 0.f, 0.f, 0.f, 0.f};
#pragma unroll
    for (int i = 0; i < 12; i++) {
      *reinterpret_cast<uint4*>(As + (rg * 12 + i) * FW_LD + cg * 8) = va[i];
      sa[0] += bf_lo(va[i].x); sa[1] += bf_hi(va[i].x); sa[2] += bf_lo(va[i].y); sa[3] += bf_hi(va[i].y);
      sa[4] += bf_lo(va[i].z); sa[5] += bf_hi(va[i].z); sa[6] += bf_lo(va[i].w); sa[7] += bf_hi(va[i].w);
      sb[0] += bf_lo(vb[i].x); sb[1] += bf_hi(vb[i].x); sb[2] += bf_lo(vb[i].y); sb[3] += bf_hi(vb[i].y);
      sb[4] += bf_lo(vb[i].z); sb[5] += bf_hi(vb[i].z); sb[6] += bf_lo(vb[i].w); sb[7] += bf_hi(vb[i].w);
    }
#pragma unroll
    for (int e = 0; e < 8; e++) { part[rg * CH + cg * 8 + e] = sa[e]; part2[rg * CH + cg * 8 + e] = sb[e]; }
  }
  __syncthreads();
  if (tid < CH) {
    float s = 0.f, s2 = 0.f;
#pragma unroll
    for (int r = 0; r < 16; r++) { s += part[r * CH + tid]; s2 += part2[r * CH + tid]; }
    cm[tid] = s * (1.0f / CH);
    const float cmB = s2 * (1.0f / CH);
#pragma unroll
    for (int n = 0; n < 16; n++)
      Bs[n * 196 + tid] = isM ? (__bfloat162float(wqkv[(n0 + n) * 3 * CH + CH + tid]) - cmB) : __bfloat162float(wo[tid * CH + n0 + n]);
  }
  __syncthreads();
  const int k = tid >> 1, nh = (tid & 1) * 8;
  float acc[8];
#pragma unroll
  for (int n = 0; n < 8; n++) acc[n] = 0.f;
#pragma unroll 4
  for (int c = 0; c < CH; c += 4) {
    const uint2 u = *reinterpret_cast<const uint2*>(As + k * FW_LD + c);
    const float4 m4 = *reinterpret_cast<const float4*>(cm + c);
    const float a0 = bf_lo(u.x) - m4.x, a1 = bf_hi(u.x) - m4.y, a2 = bf_lo(u.y) - m4.z, a3 = bf_hi(u.y) - m4.w;
#pragma unroll
    for (int n = 0; n < 8; n++) {
      const float4 b = *reinterpret_cast<const float4*>(Bs + (nh + n) * 196 + c);
      acc[n] = fmaf(a0, b.x, acc[n]); acc[n] = fmaf(a1, b.y, acc[n]);
      acc[n] = fmaf(a2, b.z, acc[n]); acc[n] = fmaf(a3, b.w, acc[n]);
    }
  }
  const int p = k >> 6, kc = k & 63;
#pragma unroll
  for (int n = 0; n < 8; n++) {
    const int nn = n0 + nh + n;
    g_w[mat][p * (CH * 64) + nn * 64 + (((kc >> 3) ^ (nn & 7)) << 3) + (kc & 7)] = __float2bfloat16(acc[n]);
  }
}
constexpr int FW_SMEM = CH * FW_LD * 2 + (32 * CH + CH + 16 * 196) * 4;

struct Params {
  int role;
};

__device__ __forceinline__ uint32_t frag_addr(uint32_t slot_rowoff, uint32_t sw, int hiblk, int kk) {
  const int ci = 2 * kk + hiblk;
  return slot_rowoff + (ci >> 3) * PANEL_X + ((((uint32_t)ci & 7u) ^ sw) << 4);
}

__device__ __forceinline__ float row_rstd(uint32_t slot, int w, int lane) {
  const int row = 16 * w + (lane >> 1), half = lane & 1;
  const uint32_t rbase = slot + row * 128, sw = row & 7;
  float s0 = 0.f, s1 = 0.f, s2 = 0.f, s3 = 0.f, q0 = 0.f, q1 = 0.f, q2 = 0.f, q3 = 0.f;
#pragma unroll
  for (int i = 0; i < 12; i++) {
    const int c = half * 12 + i;
    const uint4 v = lds128(rbase + (c >> 3) * PANEL_X + ((((uint32_t)c & 7u) ^ sw) << 4));
    float lo, hi;
    lo = bf_lo(v.x); hi = bf_hi(v.x); s0 += lo; s1 += hi; q0 = fmaf(lo, lo, q0); q1 = fmaf(hi, hi, q1);
    lo = bf_lo(v.y); hi = bf_hi(v.y); s2 += lo; s3 += hi; q2 = fmaf(lo, lo, q2); q3 = fmaf(hi, hi, q3);
    lo = bf_lo(v.z); hi = bf_hi(v.z); s0 += lo; s1 += hi; q0 = fmaf(lo, lo, q0); q1 = fmaf(hi, hi, q1);
    lo = bf_lo(v.w); hi = bf_hi(v.w); s2 += lo; s3 += hi; q2 = fmaf(lo, lo, q2); q3 = fmaf(hi, hi, q3);
  }
  float s = (s0 + s1) + (s2 + s3), ss = (q0 + q1) + (q2 + q3);
  s += __shfl_xor_sync(0xffffffffu, s, 1);
  ss += __shfl_xor_sync(0xffffffffu, ss, 1);
  const float mean = s * (1.0f / CH);
  const float var = fmaxf(ss * (1.0f / CH) - mean * mean, 0.f);
  return rsqrtf(var + 1e-5f);
}

__global__ void __launch_bounds__(NWG * 128 + 128, 1)
swin_main_kernel(const __grid_constant__ CUtensorMap mapA_in, const __grid_constant__ CUtensorMap mapA_out,
                 const __grid_constant__ CUtensorMap mapB_in, const __grid_constant__ CUtensorMap mapB_out, const int num_a) {
  const int role = (int)blockIdx.x < num_a ? 0 : 1;
  const CUtensorMap* pmap_in = role == 0 ? &mapA_in : &mapB_in;
  const CUtensorMap* pmap_out = role == 0 ? &mapA_out : &mapB_out;
  extern __shared__ __align__(1024) uint8_t smem_raw[];
  const uint32_t sbase = smem_u32(smem_raw);
  const int tid = threadIdx.x, wg = tid >> 7, t128 = tid & 127, w = t128 >> 5, lane = tid & 31;
  const int g = lane >> 2, q = lane & 3;

  const uint32_t bar_w = sbase + SMEM_MISC;
  float* rbuf = reinterpret_cast<float*>(smem_raw + SMEM_RBUF) + wg * 64;

  if (tid == 0) {
    mbar_init(bar_w, 1);
    for (int i = 0; i < NSLOT; i++) { mbar_init(sbase + SMEM_MISC + 8 + 8 * i, 1); mbar_init(sbase + SMEM_MISC + 64 + 8 * i, 128); }
    asm volatile("fence.mbarrier_init.release.cluster;" ::: "memory");
  }
  for (int i = tid; i < NSLOT * SLOT_BYTES / 16; i += NWG * 128 + 128)
    *reinterpret_cast<uint4*>(smem_raw + SMEM_SLOT + i * 16) = make_uint4(0, 0, 0, 0);
  fence_proxy_async();
  __syncthreads();

  const int nunits = role == 0 ? NTILE_A : NUNIT_B;
  const int ustride = role == 0 ? num_a : (int)gridDim.x - num_a;
  const int ubase = role == 0 ? (int)blockIdx.x : (int)blockIdx.x - num_a;
  const int nj = (nunits - ubase + ustride - 1) / ustride;
  const uint32_t tx_bytes = role == 0 ? SLOT_BYTES : 3 * 49 * 128;

  auto coords = [&](int j, int& c1, int& c2, int& c3) {
    const int u = ubase + j * ustride;
    if (role == 0) { c1 = 0; c2 = (u % 14) * 16; c3 = u / 14; }
    else { const int t = u & 3, wx = (u >> 2) & 31, wy = u >> 7; c1 = wx * 7; c2 = wy * 7; c3 = t; }
  };
  auto issue_load = [&](int j) {
    int c1, c2, c3; coords(j, c1, c2, c3);
    if (role != 0) {
      const unsigned int* cnt = &g_band_cnt[c2 / 7];
      unsigned int v; int spins = 0;
      do {
        asm volatile("ld.acquire.gpu.global.u32 %0, [%1];" : "=r"(v) : "l"(cnt) : "memory");
        if (v >= 98u) break;
        __nanosleep(64);
      } while (++spins < (1 << 22));
      asm volatile("fence.proxy.async.global;" ::: "memory");
    }
    const int sl = j % NSLOT;
    const uint32_t bar = sbase + SMEM_MISC + 8 + 8 * sl;
    mbar_expect_tx(bar, tx_bytes);
#pragma unroll
    for (int p = 0; p < 3; p++) tma_load_4d(sbase + SMEM_SLOT + sl * SLOT_BYTES + p * PANEL_X, pmap_in, p * 64, c1, c2, c3, bar);
  };
  auto prefetch_l2 = [&](int j) {
    if (role == 0 && j < nj) {
      int c1, c2, c3; coords(j, c1, c2, c3);
#pragma unroll
      for (int p = 0; p < 3; p++) tma_prefetch_4d(pmap_in, p * 64, c1, c2, c3);
    }
  };

  if (tid >= NWG * 128) {
    asm volatile("setmaxnreg.dec.sync.aligned.u32 40;");
    if (tid == NWG * 128) {
      mbar_expect_tx(bar_w, 2 * WMAT_BYTES);
      bulk_load(sbase + SMEM_W0, &g_w[role * 2][0], WMAT_BYTES, bar_w);
      bulk_load(sbase + SMEM_W1, &g_w[role * 2 + 1][0], WMAT_BYTES, bar_w);
      for (int j = 0; j < NSLOT && j < nj; j++) issue_load(j);
      prefetch_l2(NSLOT); prefetch_l2(NSLOT + 1);
      for (int j = 0; j < nj; j++) {
        const int sl = j % NSLOT;
        mbar_wait(sbase + SMEM_MISC + 64 + 8 * sl, (j / NSLOT) & 1);
        int c1, c2, c3; coords(j, c1, c2, c3);
#pragma unroll
        for (int p = 0; p < 3; p++) tma_store_4d(pmap_out, sbase + SMEM_SLOT + sl * SLOT_BYTES + p * PANEL_X, p * 64, c1, c2, c3);
        bulk_commit();
        bulk_wait_read0();
        if (j + NSLOT < nj) issue_load(j + NSLOT);
        prefetch_l2(j + NSLOT + 2);
        if (role == 0) {
          bulk_wait0();
          asm volatile("fence.proxy.async.global;" ::: "memory");
          __threadfence();
          atomicAdd(&g_band_cnt[c3 / 7], 1u);
        }
      }
      bulk_wait0();
    }
    return;
  }
  asm volatile("setmaxnreg.inc.sync.aligned.u32 232;");
  mbar_wait(bar_w, 0);

  const int blk = lane >> 3;
  const int frow = 16 * w + (lane & 7) + ((blk & 1) << 3);
  const uint32_t fsw = frow & 7;
  const int fhi = blk >> 1;

  const uint64_t dW0 = make_desc(sbase + SMEM_W0, 16, 1024);
  const uint64_t dW1 = make_desc(sbase + SMEM_W1, 16, 1024);

  const float scale_l2e = 0.07216878364870322f * 1.4426950408889634f;

  const int nturn = 2 * ((nj + 1) / 2);
  if (wg == 1) { turn_pass(1); turn_wait(1); turn_pass(1); }
  for (int j = wg; j < nj; j += NWG) {
    const int sl = j % NSLOT;
    const uint32_t slot = sbase + SMEM_SLOT + sl * SLOT_BYTES;
    const uint32_t frowoff = slot + frow * 128;
    const uint64_t dX = make_desc(slot, 16, 1024);
    const uint64_t dXmn = make_desc(slot, PANEL_X, 1024);
    PH(0);
    mbar_wait(sbase + SMEM_MISC + 8 + 8 * sl, (j / NSLOT) & 1);
    PH(1);

    float acc[96];
    turn_wait(wg);
    wgmma_fence();
#pragma unroll
    for (int kk = 0; kk < 12; kk++) {
      const uint32_t off = (kk >> 2) * PANEL_X + (kk & 3) * 32;
      const uint32_t offw = (kk >> 2) * PANEL_W + (kk & 3) * 32;
      wgmma_n192_ss(acc, dX + (off >> 4), dW0 + (offw >> 4), kk);
    }
    wgmma_commit();
    turn_pass(wg);
    PH(2);
    const float rmine = row_rstd(slot, w, lane);
    PH(3);
    uint32_t fr[48], xf[48];

    if (role == 0) {
      wgmma_wait0(); acc_fence(acc);
      PH(4);
#pragma unroll
      for (int i = 0; i < 48; i++) fr[i] = pack_bf16(acc[2 * i], acc[2 * i + 1]);
#pragma unroll
      for (int kk = 0; kk < 12; kk++) ldsm_x4(frag_addr(frowoff, fsw, fhi, kk), xf[4 * kk], xf[4 * kk + 1], xf[4 * kk + 2], xf[4 * kk + 3]);
#pragma unroll
      for (int kk = 0; kk < 12; kk++) {
#pragma unroll
        for (int i = 0; i < 8; i++) acc[8 * kk + i] = 0.f;
        mma_16816(acc[8 * kk + 0], acc[8 * kk + 1], acc[8 * kk + 2], acc[8 * kk + 3], fr[4 * kk], fr[4 * kk + 1], fr[4 * kk + 2], fr[4 * kk + 3], xf[4 * kk], xf[4 * kk + 2]);
        mma_16816(acc[8 * kk + 4], acc[8 * kk + 5], acc[8 * kk + 6], acc[8 * kk + 7], fr[4 * kk], fr[4 * kk + 1], fr[4 * kk + 2], fr[4 * kk + 3], xf[4 * kk + 1], xf[4 * kk + 3]);
      }
      float d0[4], d1[4];
      {
        float t0 = 0.f, t1 = 0.f, t2 = 0.f, t3 = 0.f, u0 = 0.f, u1 = 0.f, u2 = 0.f, u3 = 0.f;
#pragma unroll
        for (int kk = 0; kk < 12; kk += 2) {
          t0 += acc[8 * kk + 0]; t1 += acc[8 * kk + 1]; t2 += acc[8 * kk + 6]; t3 += acc[8 * kk + 7];
          u0 += acc[8 * kk + 8]; u1 += acc[8 * kk + 9]; u2 += acc[8 * kk + 14]; u3 += acc[8 * kk + 15];
        }
        d0[0] = t0 + u0; d0[1] = t1 + u1; d1[2] = t2 + u2; d1[3] = t3 + u3;
      }
      const float rA = __shfl_sync(0xffffffffu, rmine, 2 * g);
      const float rB = __shfl_sync(0xffffffffu, rmine, 2 * g + 16);
      const float k0 = __shfl_sync(0xffffffffu, rmine, 4 * q);
      const float k1 = __shfl_sync(0xffffffffu, rmine, 4 * q + 2);
      const float k2 = __shfl_sync(0xffffffffu, rmine, 4 * q + 16);
      const float k3 = __shfl_sync(0xffffffffu, rmine, 4 * q + 18);
      const bool valid = (g >> 2) == (q >> 1);
      float sa0 = d0[0] * k0 * (rA * scale_l2e), sa1 = d0[1] * k1 * (rA * scale_l2e);
      float sb0 = d1[2] * k2 * (rB * scale_l2e), sb1 = d1[3] * k3 * (rB * scale_l2e);
      float ma = fmaxf(sa0, sa1), mb = fmaxf(sb0, sb1);
      ma = fmaxf(ma, __shfl_xor_sync(0xffffffffu, ma, 1));
      mb = fmaxf(mb, __shfl_xor_sync(0xffffffffu, mb, 1));
      const float ea0 = exp2f(sa0 - ma), ea1 = exp2f(sa1 - ma);
      const float eb0 = exp2f(sb0 - mb), eb1 = exp2f(sb1 - mb);
      float suma = ea0 + ea1, sumb = eb0 + eb1;
      suma += __shfl_xor_sync(0xffffffffu, suma, 1);
      sumb += __shfl_xor_sync(0xffffffffu, sumb, 1);
      const float ia = __fdividef(1.f, suma), ib = __fdividef(1.f, sumb);
      const uint32_t pa0 = valid ? pack_bf16(ea0 * ia * k0, ea1 * ia * k1) : 0u;
      const uint32_t pa3 = valid ? pack_bf16(eb0 * ib * k2, eb1 * ib * k3) : 0u;
      PH(5);
#pragma unroll
      for (int hh = 0; hh < 2; hh++) {
        uint32_t bt[24];
#pragma unroll
        for (int jj = 0; jj < 6; jj++) ldsm_x4_t(frag_addr(frowoff, fsw, fhi, hh * 6 + jj), bt[4 * jj], bt[4 * jj + 1], bt[4 * jj + 2], bt[4 * jj + 3]);
#pragma unroll
        for (int jj = 0; jj < 6; jj++) {
          const int o = 8 * (hh * 6 + jj);
          acc[o + 0] = 0.f; acc[o + 1] = 0.f; acc[o + 2] = 0.f; acc[o + 3] = 0.f;
          acc[o + 4] = 0.f; acc[o + 5] = 0.f; acc[o + 6] = 0.f; acc[o + 7] = 0.f;
          mma_16816(acc[o + 0], acc[o + 1], acc[o + 2], acc[o + 3], pa0, 0u, 0u, pa3, bt[4 * jj], bt[4 * jj + 1]);
          mma_16816(acc[o + 4], acc[o + 5], acc[o + 6], acc[o + 7], pa0, 0u, 0u, pa3, bt[4 * jj + 2], bt[4 * jj + 3]);
        }
      }
    } else {
      if ((lane & 1) == 0) rbuf[16 * w + (lane >> 1)] = rmine;
      wg_bar(1 + wg);
      wgmma_wait0(); acc_fence(acc);
      PH(4);
#pragma unroll
      for (int i = 0; i < 48; i++) fr[i] = pack_bf16(acc[2 * i], acc[2 * i + 1]);
      float s[28], s2[28];
      wgmma_fence();
#pragma unroll
      for (int kk = 0; kk < 12; kk += 2) {
        const uint32_t off = (kk >> 2) * PANEL_X + (kk & 3) * 32;
        wgmma_n56_rs(s, fr[4 * kk], fr[4 * kk + 1], fr[4 * kk + 2], fr[4 * kk + 3], dX + (off >> 4), kk);
        wgmma_n56_rs(s2, fr[4 * kk + 4], fr[4 * kk + 5], fr[4 * kk + 6], fr[4 * kk + 7], dX + ((off + 32) >> 4), kk);
      }
      wgmma_commit();
      float rj[14];
#pragma unroll
      for (int j = 0; j < 7; j++) {
        const float2 v = *reinterpret_cast<const float2*>(&rbuf[8 * j + 2 * q]);
        rj[2 * j] = v.x; rj[2 * j + 1] = v.y;
      }
      const float ri0 = rbuf[16 * w + g] * scale_l2e, ri1 = rbuf[16 * w + g + 8] * scale_l2e;
      wgmma_wait0(); acc_fence(s); acc_fence(s2);
#pragma unroll
      for (int i = 0; i < 28; i++) s[i] += s2[i];
      PH(5);
      float m0 = -INFINITY, m1 = -INFINITY;
#pragma unroll
      for (int j = 0; j < 7; j++) {
#pragma unroll
        for (int e = 0; e < 2; e++) {
          const bool ok = (j < 6) || (2 * q + e == 0);
          float v0 = s[4 * j + e] * rj[2 * j + e] * ri0;
          float v1 = s[4 * j + 2 + e] * rj[2 * j + e] * ri1;
          v0 = ok ? v0 : -INFINITY; v1 = ok ? v1 : -INFINITY;
          s[4 * j + e] = v0; s[4 * j + 2 + e] = v1;
          m0 = fmaxf(m0, v0); m1 = fmaxf(m1, v1);
        }
      }
      m0 = fmaxf(m0, __shfl_xor_sync(0xffffffffu, m0, 1)); m0 = fmaxf(m0, __shfl_xor_sync(0xffffffffu, m0, 2));
      m1 = fmaxf(m1, __shfl_xor_sync(0xffffffffu, m1, 1)); m1 = fmaxf(m1, __shfl_xor_sync(0xffffffffu, m1, 2));
      float sum0 = 0.f, sum1 = 0.f;
#pragma unroll
      for (int j = 0; j < 7; j++) {
#pragma unroll
        for (int e = 0; e < 2; e++) {
          const float e0 = exp2f(s[4 * j + e] - m0), e1 = exp2f(s[4 * j + 2 + e] - m1);
          s[4 * j + e] = e0; s[4 * j + 2 + e] = e1;
          sum0 += e0; sum1 += e1;
        }
      }
      sum0 += __shfl_xor_sync(0xffffffffu, sum0, 1); sum0 += __shfl_xor_sync(0xffffffffu, sum0, 2);
      sum1 += __shfl_xor_sync(0xffffffffu, sum1, 1); sum1 += __shfl_xor_sync(0xffffffffu, sum1, 2);
      const float i0 = __fdividef(1.f, sum0), i1 = __fdividef(1.f, sum1);
      uint32_t pa[16];
#pragma unroll
      for (int j = 0; j < 7; j++) {
        pa[(j >> 1) * 4 + (j & 1) * 2 + 0] = pack_bf16(s[4 * j] * i0 * rj[2 * j], s[4 * j + 1] * i0 * rj[2 * j + 1]);
        pa[(j >> 1) * 4 + (j & 1) * 2 + 1] = pack_bf16(s[4 * j + 2] * i1 * rj[2 * j], s[4 * j + 3] * i1 * rj[2 * j + 1]);
      }
      pa[14] = 0u; pa[15] = 0u;
      PH(6);
      wgmma_fence();
#pragma unroll
      for (int kk = 0; kk < 4; kk++)
        wgmma_n192_rs_tb(acc, pa[4 * kk], pa[4 * kk + 1], pa[4 * kk + 2], pa[4 * kk + 3], dXmn + ((kk * 2048) >> 4), kk);
      wgmma_commit();
      wgmma_wait0(); acc_fence(acc);
    }

    PH(7);
#pragma unroll
    for (int i = 0; i < 48; i++) fr[i] = pack_bf16(acc[2 * i], acc[2 * i + 1]);
    turn_wait(wg);
    wgmma_fence();
#pragma unroll
    for (int kk = 0; kk < 12; kk++) {
      const uint32_t offw = (kk >> 2) * PANEL_W + (kk & 3) * 32;
      wgmma_n192_rs(acc, fr[4 * kk], fr[4 * kk + 1], fr[4 * kk + 2], fr[4 * kk + 3], dW1 + (offw >> 4), kk);
    }
    wgmma_commit();
    turn_pass(wg);
    if (role != 0) {
#pragma unroll
      for (int kk = 0; kk < 12; kk++) ldsm_x4(frag_addr(frowoff, fsw, fhi, kk), xf[4 * kk], xf[4 * kk + 1], xf[4 * kk + 2], xf[4 * kk + 3]);
    }
    wgmma_wait0(); acc_fence(acc);
    PH(8);
    wg_bar(1 + wg);
    PH(9);
#pragma unroll
    for (int kk = 0; kk < 12; kk++) {
      const uint32_t o0 = add_bf16x2(xf[4 * kk + 0], pack_bf16(acc[8 * kk + 0], acc[8 * kk + 1]));
      const uint32_t o1 = add_bf16x2(xf[4 * kk + 1], pack_bf16(acc[8 * kk + 2], acc[8 * kk + 3]));
      const uint32_t o2 = add_bf16x2(xf[4 * kk + 2], pack_bf16(acc[8 * kk + 4], acc[8 * kk + 5]));
      const uint32_t o3 = add_bf16x2(xf[4 * kk + 3], pack_bf16(acc[8 * kk + 6], acc[8 * kk + 7]));
      stsm_x4(frag_addr(frowoff, fsw, fhi, kk), o0, o1, o2, o3);
    }
    PH(10);
    fence_proxy_async();
    mbar_arrive(sbase + SMEM_MISC + 64 + 8 * sl);
    PH(11);
  }
  for (int t = 2 * ((nj - wg + 1) / 2); t < nturn; t++) { turn_wait(wg); turn_pass(wg); }
  if (wg == 0) turn_pass(0);
}

typedef CUresult (*EncodeTiledFn)(CUtensorMap*, CUtensorMapDataType, cuuint32_t, void*, const cuuint64_t*, const cuuint64_t*,
                                  const cuuint32_t*, const cuuint32_t*, CUtensorMapInterleave, CUtensorMapSwizzle,
                                  CUtensorMapL2promotion, CUtensorMapFloatOOBfill);

bool make_map(EncodeTiledFn fn, CUtensorMap* m, void* base, bool pixel_major) {
  cuuint64_t dims[4]; cuuint64_t strides[3]; cuuint32_t box[4]; cuuint32_t es[4] = {1, 1, 1, 1};
  const cuuint64_t sC = (cuuint64_t)CH * 2, sW = sC * WW, sT = sW * HH;
  if (pixel_major) {
    dims[0] = CH; dims[1] = TT; dims[2] = WW; dims[3] = HH;
    strides[0] = sT; strides[1] = sC; strides[2] = sW;
    box[0] = 64; box[1] = 4; box[2] = 16; box[3] = 1;
  } else {
    dims[0] = CH; dims[1] = WW; dims[2] = HH; dims[3] = TT;
    strides[0] = sC; strides[1] = sW; strides[2] = sT;
    box[0] = 64; box[1] = 7; box[2] = 7; box[3] = 1;
  }
  return fn(m, CU_TENSOR_MAP_DATA_TYPE_BFLOAT16, 4, base, dims, strides, box, es, CU_TENSOR_MAP_INTERLEAVE_NONE,
            CU_TENSOR_MAP_SWIZZLE_128B, CU_TENSOR_MAP_L2_PROMOTION_L2_256B, CU_TENSOR_MAP_FLOAT_OOB_FILL_NONE) == CUDA_SUCCESS;
}

}

extern "C" void kernel_launch(void* const* d_in, const int* in_sizes, int n_in, void* d_out, int out_size) {
  const __nv_bfloat16* x = (const __nv_bfloat16*)d_in[0];
  const __nv_bfloat16* wqkv_t = (const __nv_bfloat16*)d_in[1];
  const __nv_bfloat16* wo_t = (const __nv_bfloat16*)d_in[2];
  const __nv_bfloat16* wqkv_s = (const __nv_bfloat16*)d_in[3];
  const __nv_bfloat16* wo_s = (const __nv_bfloat16*)d_in[4];

  static bool init = false;
  static CUtensorMap mA_in, mA_out, mB_in, mB_out;
  static void* last_x = nullptr; static void* last_out = nullptr;
  static int nsm = 132;
  if (!init || last_x != d_in[0] || last_out != d_out) {
    void* fnp = nullptr; cudaDriverEntryPointQueryResult qr;
    cudaGetDriverEntryPoint("cuTensorMapEncodeTiled", &fnp, cudaEnableDefault, &qr);
    EncodeTiledFn fn = (EncodeTiledFn)fnp;
    void* x1p = nullptr; cudaGetSymbolAddress(&x1p, g_x1);
    make_map(fn, &mA_in, (void*)x, true);
    make_map(fn, &mA_out, x1p, true);
    make_map(fn, &mB_in, x1p, false);
    make_map(fn, &mB_out, d_out, false);
    cudaFuncSetAttribute(fold_weights_kernel, cudaFuncAttributeMaxDynamicSharedMemorySize, FW_SMEM);
    cudaFuncSetAttribute(swin_main_kernel, cudaFuncAttributeMaxDynamicSharedMemorySize, SMEM_TOTAL);
    cudaDeviceGetAttribute(&nsm, cudaDevAttrMultiProcessorCount, 0);
    init = true; last_x = d_in[0]; last_out = d_out;
  }
  fold_weights_kernel<<<dim3(12, 4), 384, FW_SMEM>>>(wqkv_t, wo_t, wqkv_s, wo_s);
  swin_main_kernel<<<nsm, NWG * 128 + 128, SMEM_TOTAL>>>(mA_in, mA_out, mB_in, mB_out, NUM_A);
}
```

```cpp
#include <cuda_runtime.h>
#include <cuda_bf16.h>
#include <cuda.h>
#include <stdint.h>

namespace {

constexpr int CH = 192;
constexpr int TT = 4, HH = 224, WW = 224;
constexpr int NTOK = TT * HH * WW;
constexpr int PANEL_X = 64 * 128;
constexpr int SLOT_BYTES = 3 * PANEL_X;
constexpr int PANEL_W = 192 * 128;
constexpr int WMAT_BYTES = 3 * PANEL_W;
constexpr int NWG = 2;
constexpr int NSLOT = 3;
constexpr int SMEM_W0 = 0;
constexpr int SMEM_W1 = WMAT_BYTES;
constexpr int SMEM_SLOT = 2 * WMAT_BYTES;
constexpr int SMEM_MISC = SMEM_SLOT + NSLOT * SLOT_BYTES;
constexpr int SMEM_RBUF = SMEM_MISC + 128;
constexpr int SMEM_TOTAL = SMEM_RBUF + NWG * 64 * 4;

constexpr int NTILE_A = HH * (WW / 16);
constexpr int NUNIT_B = 32 * 32 * 4;
#define NUM_A 56

__device__ __nv_bfloat16 g_x1[(size_t)NTOK * CH];
__device__ unsigned int g_band_cnt[32];
__device__ __align__(1024) __nv_bfloat16 g_w[4][CH * CH];

#define PH(i) do {} while (0)
__device__ __forceinline__ uint32_t smem_u32(const void* p) { return (uint32_t)__cvta_generic_to_shared(p); }

__device__ __forceinline__ void mbar_init(uint32_t bar, uint32_t count) {
  asm volatile("mbarrier.init.shared::cta.b64 [%0], %1;" :: "r"(bar), "r"(count));
}
__device__ __forceinline__ void mbar_expect_tx(uint32_t bar, uint32_t bytes) {
  asm volatile("mbarrier.arrive.expect_tx.shared::cta.b64 _, [%0], %1;" :: "r"(bar), "r"(bytes) : "memory");
}
__device__ __forceinline__ void mbar_arrive(uint32_t bar) {
  asm volatile("mbarrier.arrive.shared::cta.b64 _, [%0];" :: "r"(bar) : "memory");
}
__device__ __forceinline__ void mbar_wait(uint32_t bar, uint32_t parity) {
  asm volatile(
    "{\n.reg .pred p;\n"
    "WAIT_%=:\n"
    "mbarrier.try_wait.parity.shared::cta.b64 p, [%0], %1;\n"
    "@p bra DONE_%=;\n"
    "bra WAIT_%=;\n"
    "DONE_%=:\n}\n" :: "r"(bar), "r"(parity) : "memory");
}
__device__ __forceinline__ void tma_load_4d(uint32_t dst, const CUtensorMap* map, int c0, int c1, int c2, int c3, uint32_t bar) {
  asm volatile("cp.async.bulk.tensor.4d.shared::cluster.global.tile.mbarrier::complete_tx::bytes [%0], [%1, {%2, %3, %4, %5}], [%6];"
    :: "r"(dst), "l"(map), "r"(c0), "r"(c1), "r"(c2), "r"(c3), "r"(bar) : "memory");
}
__device__ __forceinline__ void tma_prefetch_4d(const CUtensorMap* map, int c0, int c1, int c2, int c3) {
  asm volatile("cp.async.bulk.prefetch.tensor.4d.L2.global.tile [%0, {%1, %2, %3, %4}];"
    :: "l"(map), "r"(c0), "r"(c1), "r"(c2), "r"(c3) : "memory");
}
__device__ __forceinline__ void tma_store_4d(const CUtensorMap* map, uint32_t src, int c0, int c1, int c2, int c3) {
  asm volatile("cp.async.bulk.tensor.4d.global.shared::cta.tile.bulk_group [%0, {%1, %2, %3, %4}], [%5];"
    :: "l"(map), "r"(c0), "r"(c1), "r"(c2), "r"(c3), "r"(src) : "memory");
}
__device__ __forceinline__ void bulk_load(uint32_t dst, const void* src, uint32_t bytes, uint32_t bar) {
  asm volatile("cp.async.bulk.shared::cluster.global.mbarrier::complete_tx::bytes [%0], [%1], %2, [%3];"
    :: "r"(dst), "l"(src), "r"(bytes), "r"(bar) : "memory");
}
__device__ __forceinline__ void bulk_commit() { asm volatile("cp.async.bulk.commit_group;" ::: "memory"); }
__device__ __forceinline__ void bulk_wait_read0() { asm volatile("cp.async.bulk.wait_group.read 0;" ::: "memory"); }
__device__ __forceinline__ void bulk_wait0() { asm volatile("cp.async.bulk.wait_group 0;" ::: "memory"); }
__device__ __forceinline__ void fence_proxy_async() { asm volatile("fence.proxy.async.shared::cta;" ::: "memory"); }
__device__ __forceinline__ void wg_bar(int id) { asm volatile("bar.sync %0, 128;" :: "r"(id) : "memory"); }
__device__ __forceinline__ void wgmma_fence() { asm volatile("wgmma.fence.sync.aligned;" ::: "memory"); }
__device__ __forceinline__ void wgmma_commit() { asm volatile("wgmma.commit_group.sync.aligned;" ::: "memory"); }
__device__ __forceinline__ void wgmma_wait0() { asm volatile("wgmma.wait_group.sync.aligned 0;" ::: "memory"); }

__device__ __forceinline__ uint64_t make_desc(uint32_t saddr, uint32_t lbo, uint32_t sbo) {
  return (uint64_t)((saddr & 0x3FFFF) >> 4) | ((uint64_t)((lbo & 0x3FFFF) >> 4) << 16) |
         ((uint64_t)((sbo & 0x3FFFF) >> 4) << 32) | ((uint64_t)1 << 62);
}
__device__ __forceinline__ uint32_t pack_bf16(float lo, float hi) {
  uint32_t r; asm("cvt.rn.bf16x2.f32 %0, %1, %2;" : "=r"(r) : "f"(hi), "f"(lo)); return r;
}
__device__ __forceinline__ uint32_t add_bf16x2(uint32_t a, uint32_t b) {
  uint32_t r; asm("add.rn.bf16x2 %0, %1, %2;" : "=r"(r) : "r"(a), "r"(b)); return r;
}
__device__ __forceinline__ float bf_lo(uint32_t u) { return __uint_as_float(u << 16); }
__device__ __forceinline__ float bf_hi(uint32_t u) { return __uint_as_float(u & 0xffff0000u); }
__device__ __forceinline__ void ldsm_x4(uint32_t addr, uint32_t& r0, uint32_t& r1, uint32_t& r2, uint32_t& r3) {
  asm volatile("ldmatrix.sync.aligned.m8n8.x4.shared.b16 {%0,%1,%2,%3}, [%4];"
    : "=r"(r0), "=r"(r1), "=r"(r2), "=r"(r3) : "r"(addr) : "memory");
}
__device__ __forceinline__ void ldsm_x4_t(uint32_t addr, uint32_t& r0, uint32_t& r1, uint32_t& r2, uint32_t& r3) {
  asm volatile("ldmatrix.sync.aligned.m8n8.x4.trans.shared.b16 {%0,%1,%2,%3}, [%4];"
    : "=r"(r0), "=r"(r1), "=r"(r2), "=r"(r3) : "r"(addr) : "memory");
}
__device__ __forceinline__ void stsm_x4(uint32_t addr, uint32_t r0, uint32_t r1, uint32_t r2, uint32_t r3) {
  asm volatile("stmatrix.sync.aligned.m8n8.x4.shared.b16 [%0], {%1,%2,%3,%4};"
    :: "r"(addr), "r"(r0), "r"(r1), "r"(r2), "r"(r3) : "memory");
}
__device__ __forceinline__ void mma_16816(float& d0, float& d1, float& d2, float& d3,
                                          uint32_t a0, uint32_t a1, uint32_t a2, uint32_t a3, uint32_t b0, uint32_t b1) {
  asm volatile("mma.sync.aligned.m16n8k16.row.col.f32.bf16.bf16.f32 {%0,%1,%2,%3}, {%4,%5,%6,%7}, {%8,%9}, {%0,%1,%2,%3};"
    : "+f"(d0), "+f"(d1), "+f"(d2), "+f"(d3) : "r"(a0), "r"(a1), "r"(a2), "r"(a3), "r"(b0), "r"(b1));
}
__device__ __forceinline__ uint4 lds128(uint32_t addr) {
  uint4 v; asm volatile("ld.shared.v4.u32 {%0,%1,%2,%3}, [%4];" : "=r"(v.x), "=r"(v.y), "=r"(v.z), "=r"(v.w) : "r"(addr) : "memory");
  return v;
}

__device__ __forceinline__ void wgmma_n192_ss(float (&d)[96], uint64_t da, uint64_t db, int scale_d) {
  asm volatile("{\n.reg .pred p;\nsetp.ne.b32 p, %98, 0;\n"
    "wgmma.mma_async.sync.aligned.m64n192k16.f32.bf16.bf16 {%0, %1, %2, %3, %4, %5, %6, %7, %8, %9, %10, %11, %12, %13, %14, %15, %16, %17, %18, %19, %20, %21, %22, %23, %24, %25, %26, %27, %28, %29, %30, %31, %32, %33, %34, %35, %36, %37, %38, %39, %40, %41, %42, %43, %44, %45, %46, %47, %48, %49, %50, %51, %52, %53, %54, %55, %56, %57, %58, %59, %60, %61, %62, %63, %64, %65, %66, %67, %68, %69, %70, %71, %72, %73, %74, %75, %76, %77, %78, %79, %80, %81, %82, %83, %84, %85, %86, %87, %88, %89, %90, %91, %92, %93, %94, %95}, %96, %97, p, 1, 1, 0, 0;\n}\n"
    : "+f"(d[0]), "+f"(d[1]), "+f"(d[2]), "+f"(d[3]), "+f"(d[4]), "+f"(d[5]), "+f"(d[6]), "+f"(d[7]), "+f"(d[8]), "+f"(d[9]), "+f"(d[10]), "+f"(d[11]), "+f"(d[12]), "+f"(d[13]), "+f"(d[14]), "+f"(d[15]), "+f"(d[16]), "+f"(d[17]), "+f"(d[18]), "+f"(d[19]), "+f"(d[20]), "+f"(d[21]), "+f"(d[22]), "+f"(d[23]), "+f"(d[24]), "+f"(d[25]), "+f"(d[26]), "+f"(d[27]), "+f"(d[28]), "+f"(d[29]), "+f"(d[30]), "+f"(d[31]), "+f"(d[32]), "+f"(d[33]), "+f"(d[34]), "+f"(d[35]), "+f"(d[36]), "+f"(d[37]), "+f"(d[38]), "+f"(d[39]), "+f"(d[40]), "+f"(d[41]), "+f"(d[42]), "+f"(d[43]), "+f"(d[44]), "+f"(d[45]), "+f"(d[46]), "+f"(d[47]), "+f"(d[48]), "+f"(d[49]), "+f"(d[50]), "+f"(d[51]), "+f"(d[52]), "+f"(d[53]), "+f"(d[54]), "+f"(d[55]), "+f"(d[56]), "+f"(d[57]), "+f"(d[58]), "+f"(d[59]), "+f"(d[60]), "+f"(d[61]), "+f"(d[62]), "+f"(d[63]), "+f"(d[64]), "+f"(d[65]), "+f"(d[66]), "+f"(d[67]), "+f"(d[68]), "+f"(d[69]), "+f"(d[70]), "+f"(d[71]), "+f"(d[72]), "+f"(d[73]), "+f"(d[74]), "+f"(d[75]), "+f"(d[76]), "+f"(d[77]), "+f"(d[78]), "+f"(d[79]), "+f"(d[80]), "+f"(d[81]), "+f"(d[82]), "+f"(d[83]), "+f"(d[84]), "+f"(d[85]), "+f"(d[86]), "+f"(d[87]), "+f"(d[88]), "+f"(d[89]), "+f"(d[90]), "+f"(d[91]), "+f"(d[92]), "+f"(d[93]), "+f"(d[94]), "+f"(d[95])
    : "l"(da), "l"(db), "r"(scale_d));
}

__device__ __forceinline__ void wgmma_n192_rs(float (&d)[96], uint32_t a0, uint32_t a1, uint32_t a2, uint32_t a3, uint64_t db, int scale_d) {
  asm volatile("{\n.reg .pred p;\nsetp.ne.b32 p, %101, 0;\n"
    "wgmma.mma_async.sync.aligned.m64n192k16.f32.bf16.bf16 {%0, %1, %2, %3, %4, %5, %6, %7, %8, %9, %10, %11, %12, %13, %14, %15, %16, %17, %18, %19, %20, %21, %22, %23, %24, %25, %26, %27, %28, %29, %30, %31, %32, %33, %34, %35, %36, %37, %38, %39, %40, %41, %42, %43, %44, %45, %46, %47, %48, %49, %50, %51, %52, %53, %54, %55, %56, %57, %58, %59, %60, %61, %62, %63, %64, %65, %66, %67, %68, %69, %70, %71, %72, %73, %74, %75, %76, %77, %78, %79, %80, %81, %82, %83, %84, %85, %86, %87, %88, %89, %90, %91, %92, %93, %94, %95}, {%96, %97, %98, %99}, %100, p, 1, 1, 0;\n}\n"
    : "+f"(d[0]), "+f"(d[1]), "+f"(d[2]), "+f"(d[3]), "+f"(d[4]), "+f"(d[5]), "+f"(d[6]), "+f"(d[7]), "+f"(d[8]), "+f"(d[9]), "+f"(d[10]), "+f"(d[11]), "+f"(d[12]), "+f"(d[13]), "+f"(d[14]), "+f"(d[15]), "+f"(d[16]), "+f"(d[17]), "+f"(d[18]), "+f"(d[19]), "+f"(d[20]), "+f"(d[21]), "+f"(d[22]), "+f"(d[23]), "+f"(d[24]), "+f"(d[25]), "+f"(d[26]), "+f"(d[27]), "+f"(d[28]), "+f"(d[29]), "+f"(d[30]), "+f"(d[31]), "+f"(d[32]), "+f"(d[33]), "+f"(d[34]), "+f"(d[35]), "+f"(d[36]), "+f"(d[37]), "+f"(d[38]), "+f"(d[39]), "+f"(d[40]), "+f"(d[41]), "+f"(d[42]), "+f"(d[43]), "+f"(d[44]), "+f"(d[45]), "+f"(d[46]), "+f"(d[47]), "+f"(d[48]), "+f"(d[49]), "+f"(d[50]), "+f"(d[51]), "+f"(d[52]), "+f"(d[53]), "+f"(d[54]), "+f"(d[55]), "+f"(d[56]), "+f"(d[57]), "+f"(d[58]), "+f"(d[59]), "+f"(d[60]), "+f"(d[61]), "+f"(d[62]), "+f"(d[63]), "+f"(d[64]), "+f"(d[65]), "+f"(d[66]), "+f"(d[67]), "+f"(d[68]), "+f"(d[69]), "+f"(d[70]), "+f"(d[71]), "+f"(d[72]), "+f"(d[73]), "+f"(d[74]), "+f"(d[75]), "+f"(d[76]), "+f"(d[77]), "+f"(d[78]), "+f"(d[79]), "+f"(d[80]), "+f"(d[81]), "+f"(d[82]), "+f"(d[83]), "+f"(d[84]), "+f"(d[85]), "+f"(d[86]), "+f"(d[87]), "+f"(d[88]), "+f"(d[89]), "+f"(d[90]), "+f"(d[91]), "+f"(d[92]), "+f"(d[93]), "+f"(d[94]), "+f"(d[95])
    : "r"(a0), "r"(a1), "r"(a2), "r"(a3), "l"(db), "r"(scale_d));
}

__device__ __forceinline__ void wgmma_n192_rs_tb(float (&d)[96], uint32_t a0, uint32_t a1, uint32_t a2, uint32_t a3, uint64_t db, int scale_d) {
  asm volatile("{\n.reg .pred p;\nsetp.ne.b32 p, %101, 0;\n"
    "wgmma.mma_async.sync.aligned.m64n192k16.f32.bf16.bf16 {%0, %1, %2, %3, %4, %5, %6, %7, %8, %9, %10, %11, %12, %13, %14, %15, %16, %17, %18, %19, %20, %21, %22, %23, %24, %25, %26, %27, %28, %29, %30, %31, %32, %33, %34, %35, %36, %37, %38, %39, %40, %41, %42, %43, %44, %45, %46, %47, %48, %49, %50, %51, %52, %53, %54, %55, %56, %57, %58, %59, %60, %61, %62, %63, %64, %65, %66, %67, %68, %69, %70, %71, %72, %73, %74, %75, %76, %77, %78, %79, %80, %81, %82, %83, %84, %85, %86, %87, %88, %89, %90, %91, %92, %93, %94, %95}, {%96, %97, %98, %99}, %100, p, 1, 1, 1;\n}\n"
    : "+f"(d[0]), "+f"(d[1]), "+f"(d[2]), "+f"(d[3]), "+f"(d[4]), "+f"(d[5]), "+f"(d[6]), "+f"(d[7]), "+f"(d[8]), "+f"(d[9]), "+f"(d[10]), "+f"(d[11]), "+f"(d[12]), "+f"(d[13]), "+f"(d[14]), "+f"(d[15]), "+f"(d[16]), "+f"(d[17]), "+f"(d[18]), "+f"(d[19]), "+f"(d[20]), "+f"(d[21]), "+f"(d[22]), "+f"(d[23]), "+f"(d[24]), "+f"(d[25]), "+f"(d[26]), "+f"(d[27]), "+f"(d[28]), "+f"(d[29]), "+f"(d[30]), "+f"(d[31]), "+f"(d[32]), "+f"(d[33]), "+f"(d[34]), "+f"(d[35]), "+f"(d[36]), "+f"(d[37]), "+f"(d[38]), "+f"(d[39]), "+f"(d[40]), "+f"(d[41]), "+f"(d[42]), "+f"(d[43]), "+f"(d[44]), "+f"(d[45]), "+f"(d[46]), "+f"(d[47]), "+f"(d[48]), "+f"(d[49]), "+f"(d[50]), "+f"(d[51]), "+f"(d[52]), "+f"(d[53]), "+f"(d[54]), "+f"(d[55]), "+f"(d[56]), "+f"(d[57]), "+f"(d[58]), "+f"(d[59]), "+f"(d[60]), "+f"(d[61]), "+f"(d[62]), "+f"(d[63]), "+f"(d[64]), "+f"(d[65]), "+f"(d[66]), "+f"(d[67]), "+f"(d[68]), "+f"(d[69]), "+f"(d[70]), "+f"(d[71]), "+f"(d[72]), "+f"(d[73]), "+f"(d[74]), "+f"(d[75]), "+f"(d[76]), "+f"(d[77]), "+f"(d[78]), "+f"(d[79]), "+f"(d[80]), "+f"(d[81]), "+f"(d[82]), "+f"(d[83]), "+f"(d[84]), "+f"(d[85]), "+f"(d[86]), "+f"(d[87]), "+f"(d[88]), "+f"(d[89]), "+f"(d[90]), "+f"(d[91]), "+f"(d[92]), "+f"(d[93]), "+f"(d[94]), "+f"(d[95])
    : "r"(a0), "r"(a1), "r"(a2), "r"(a3), "l"(db), "r"(scale_d));
}

__device__ __forceinline__ void wgmma_n56_rs(float (&d)[28], uint32_t a0, uint32_t a1, uint32_t a2, uint32_t a3, uint64_t db, int scale_d) {
  asm volatile("{\n.reg .pred p;\nsetp.ne.b32 p, %33, 0;\n"
    "wgmma.mma_async.sync.aligned.m64n56k16.f32.bf16.bf16 {%0, %1, %2, %3, %4, %5, %6, %7, %8, %9, %10, %11, %12, %13, %14, %15, %16, %17, %18, %19, %20, %21, %22, %23, %24, %25, %26, %27}, {%28, %29, %30, %31}, %32, p, 1, 1, 0;\n}\n"
    : "+f"(d[0]), "+f"(d[1]), "+f"(d[2]), "+f"(d[3]), "+f"(d[4]), "+f"(d[5]), "+f"(d[6]), "+f"(d[7]), "+f"(d[8]), "+f"(d[9]), "+f"(d[10]), "+f"(d[11]), "+f"(d[12]), "+f"(d[13]), "+f"(d[14]), "+f"(d[15]), "+f"(d[16]), "+f"(d[17]), "+f"(d[18]), "+f"(d[19]), "+f"(d[20]), "+f"(d[21]), "+f"(d[22]), "+f"(d[23]), "+f"(d[24]), "+f"(d[25]), "+f"(d[26]), "+f"(d[27])
    : "r"(a0), "r"(a1), "r"(a2), "r"(a3), "l"(db), "r"(scale_d));
}

__device__ __forceinline__ void wgmma_n96_rs(float (&d)[48], uint32_t a0, uint32_t a1, uint32_t a2, uint32_t a3, uint64_t db, int scale_d) {
  asm volatile("{\n.reg .pred p;\nsetp.ne.b32 p, %53, 0;\n"
    "wgmma.mma_async.sync.aligned.m64n96k16.f32.bf16.bf16 {%0, %1, %2, %3, %4, %5, %6, %7, %8, %9, %10, %11, %12, %13, %14, %15, %16, %17, %18, %19, %20, %21, %22, %23, %24, %25, %26, %27, %28, %29, %30, %31, %32, %33, %34, %35, %36, %37, %38, %39, %40, %41, %42, %43, %44, %45, %46, %47}, {%48, %49, %50, %51}, %52, p, 1, 1, 0;\n}\n"
    : "+f"(d[0]), "+f"(d[1]), "+f"(d[2]), "+f"(d[3]), "+f"(d[4]), "+f"(d[5]), "+f"(d[6]), "+f"(d[7]), "+f"(d[8]), "+f"(d[9]), "+f"(d[10]), "+f"(d[11]), "+f"(d[12]), "+f"(d[13]), "+f"(d[14]), "+f"(d[15]), "+f"(d[16]), "+f"(d[17]), "+f"(d[18]), "+f"(d[19]), "+f"(d[20]), "+f"(d[21]), "+f"(d[22]), "+f"(d[23]), "+f"(d[24]), "+f"(d[25]), "+f"(d[26]), "+f"(d[27]), "+f"(d[28]), "+f"(d[29]), "+f"(d[30]), "+f"(d[31]), "+f"(d[32]), "+f"(d[33]), "+f"(d[34]), "+f"(d[35]), "+f"(d[36]), "+f"(d[37]), "+f"(d[38]), "+f"(d[39]), "+f"(d[40]), "+f"(d[41]), "+f"(d[42]), "+f"(d[43]), "+f"(d[44]), "+f"(d[45]), "+f"(d[46]), "+f"(d[47])
    : "r"(a0), "r"(a1), "r"(a2), "r"(a3), "l"(db), "r"(scale_d));
}

__device__ __forceinline__ void acc_fence(float (&d)[96]) {
  asm volatile("" : "+f"(d[0]), "+f"(d[1]), "+f"(d[2]), "+f"(d[3]), "+f"(d[4]), "+f"(d[5]), "+f"(d[6]), "+f"(d[7]), "+f"(d[8]), "+f"(d[9]), "+f"(d[10]), "+f"(d[11]), "+f"(d[12]), "+f"(d[13]), "+f"(d[14]), "+f"(d[15]), "+f"(d[16]), "+f"(d[17]), "+f"(d[18]), "+f"(d[19]), "+f"(d[20]), "+f"(d[21]), "+f"(d[22]), "+f"(d[23]), "+f"(d[24]), "+f"(d[25]), "+f"(d[26]), "+f"(d[27]), "+f"(d[28]), "+f"(d[29]), "+f"(d[30]), "+f"(d[31]), "+f"(d[32]), "+f"(d[33]), "+f"(d[34]), "+f"(d[35]), "+f"(d[36]), "+f"(d[37]), "+f"(d[38]), "+f"(d[39]), "+f"(d[40]), "+f"(d[41]), "+f"(d[42]), "+f"(d[43]), "+f"(d[44]), "+f"(d[45]), "+f"(d[46]), "+f"(d[47]), "+f"(d[48]), "+f"(d[49]), "+f"(d[50]), "+f"(d[51]), "+f"(d[52]), "+f"(d[53]), "+f"(d[54]), "+f"(d[55]), "+f"(d[56]), "+f"(d[57]), "+f"(d[58]), "+f"(d[59]), "+f"(d[60]), "+f"(d[61]), "+f"(d[62]), "+f"(d[63]), "+f"(d[64]), "+f"(d[65]), "+f"(d[66]), "+f"(d[67]), "+f"(d[68]), "+f"(d[69]), "+f"(d[70]), "+f"(d[71]), "+f"(d[72]), "+f"(d[73]), "+f"(d[74]), "+f"(d[75]), "+f"(d[76]), "+f"(d[77]), "+f"(d[78]), "+f"(d[79]), "+f"(d[80]), "+f"(d[81]), "+f"(d[82]), "+f"(d[83]), "+f"(d[84]), "+f"(d[85]), "+f"(d[86]), "+f"(d[87]), "+f"(d[88]), "+f"(d[89]), "+f"(d[90]), "+f"(d[91]), "+f"(d[92]), "+f"(d[93]), "+f"(d[94]), "+f"(d[95]) :: "memory");
}

__device__ __forceinline__ void acc_fence(float (&d)[28]) {
  asm volatile("" : "+f"(d[0]), "+f"(d[1]), "+f"(d[2]), "+f"(d[3]), "+f"(d[4]), "+f"(d[5]), "+f"(d[6]), "+f"(d[7]), "+f"(d[8]), "+f"(d[9]), "+f"(d[10]), "+f"(d[11]), "+f"(d[12]), "+f"(d[13]), "+f"(d[14]), "+f"(d[15]), "+f"(d[16]), "+f"(d[17]), "+f"(d[18]), "+f"(d[19]), "+f"(d[20]), "+f"(d[21]), "+f"(d[22]), "+f"(d[23]), "+f"(d[24]), "+f"(d[25]), "+f"(d[26]), "+f"(d[27]) :: "memory");
}

__device__ __forceinline__ void acc_fence(float (&d)[48]) {
  asm volatile("" : "+f"(d[0]), "+f"(d[1]), "+f"(d[2]), "+f"(d[3]), "+f"(d[4]), "+f"(d[5]), "+f"(d[6]), "+f"(d[7]), "+f"(d[8]), "+f"(d[9]), "+f"(d[10]), "+f"(d[11]), "+f"(d[12]), "+f"(d[13]), "+f"(d[14]), "+f"(d[15]), "+f"(d[16]), "+f"(d[17]), "+f"(d[18]), "+f"(d[19]), "+f"(d[20]), "+f"(d[21]), "+f"(d[22]), "+f"(d[23]), "+f"(d[24]), "+f"(d[25]), "+f"(d[26]), "+f"(d[27]), "+f"(d[28]), "+f"(d[29]), "+f"(d[30]), "+f"(d[31]), "+f"(d[32]), "+f"(d[33]), "+f"(d[34]), "+f"(d[35]), "+f"(d[36]), "+f"(d[37]), "+f"(d[38]), "+f"(d[39]), "+f"(d[40]), "+f"(d[41]), "+f"(d[42]), "+f"(d[43]), "+f"(d[44]), "+f"(d[45]), "+f"(d[46]), "+f"(d[47]) :: "memory");
}

constexpr int FW_LD = 200;
__global__ void __launch_bounds__(384) fold_weights_kernel(const __nv_bfloat16* __restrict__ wqkv_t, const __nv_bfloat16* __restrict__ wo_t,
                                    const __nv_bfloat16* __restrict__ wqkv_s, const __nv_bfloat16* __restrict__ wo_s) {
  extern __shared__ __align__(16) uint8_t fsm[];
  __nv_bfloat16* As = reinterpret_cast<__nv_bfloat16*>(fsm);
  float* part = reinterpret_cast<float*>(fsm + CH * FW_LD * 2);
  float* part2 = part + 16 * CH;
  float* cm = part2 + 16 * CH;
  float* Bs = cm + CH;
  const int mat = blockIdx.y, n0 = blockIdx.x * 8, tid = threadIdx.x;
  if (mat == 0 && blockIdx.x == 0 && tid < 32) g_band_cnt[tid] = 0u;
  const __nv_bfloat16* wqkv = (mat < 2) ? wqkv_t : wqkv_s;
  const __nv_bfloat16* wo = (mat < 2) ? wo_t : wo_s;
  const bool isM = (mat & 1) == 0;
  const int offA = isM ? 0 : 2 * CH;
  const int cg = tid % 24, rg = tid / 24;
  {
    uint4 va[12], vb[12];
#pragma unroll
    for (int i = 0; i < 12; i++) va[i] = *reinterpret_cast<const uint4*>(wqkv + (rg * 12 + i) * 3 * CH + offA + cg * 8);
    if (isM) {
#pragma unroll
      for (int i = 0; i < 12; i++) vb[i] = *reinterpret_cast<const uint4*>(wqkv + (rg * 12 + i) * 3 * CH + CH + cg * 8);
    } else {
#pragma unroll
      for (int i = 0; i < 12; i++) vb[i] = make_uint4(0, 0, 0, 0);
    }
    float sa[8] = {0.f, 0.f, 0.f, 0.f, 0.f, 0.f, 0.f, 0.f}, sb[8] = {0.f, 0.f, 0.f, 0.f, 0.f, 0.f, 0.f, 0.f};
#pragma unroll
    for (int i = 0; i < 12; i++) {
      *reinterpret_cast<uint4*>(As + (rg * 12 + i) * FW_LD + cg * 8) = va[i];
      sa[0] += bf_lo(va[i].x); sa[1] += bf_hi(va[i].x); sa[2] += bf_lo(va[i].y); sa[3] += bf_hi(va[i].y);
      sa[4] += bf_lo(va[i].z); sa[5] += bf_hi(va[i].z); sa[6] += bf_lo(va[i].w); sa[7] += bf_hi(va[i].w);
      sb[0] += bf_lo(vb[i].x); sb[1] += bf_hi(vb[i].x); sb[2] += bf_lo(vb[i].y); sb[3] += bf_hi(vb[i].y);
      sb[4] += bf_lo(vb[i].z); sb[5] += bf_hi(vb[i].z); sb[6] += bf_lo(vb[i].w); sb[7] += bf_hi(vb[i].w);
    }
#pragma unroll
    for (int e = 0; e < 8; e++) { part[rg * CH + cg * 8 + e] = sa[e]; part2[rg * CH + cg * 8 + e] = sb[e]; }
  }
  __syncthreads();
  if (tid < CH) {
    float s = 0.f, s2 = 0.f;
#pragma unroll
    for (int r = 0; r < 16; r++) { s += part[r * CH + tid]; s2 += part2[r * CH + tid]; }
    cm[tid] = s * (1.0f / CH);
    const float cmB = s2 * (1.0f / CH);
#pragma unroll
    for (int n = 0; n < 8; n++)
      Bs[n * 196 + tid] = isM ? (__bfloat162float(wqkv[(n0 + n) * 3 * CH + CH + tid]) - cmB) : __bfloat162float(wo[tid * CH + n0 + n]);
  }
  __syncthreads();
  const int k = tid >> 1, nh = (tid & 1) * 4;
  float acc[4];
#pragma unroll
  for (int n = 0; n < 4; n++) acc[n] = 0.f;
#pragma unroll 4
  for (int c = 0; c < CH; c += 4) {
    const uint2 u = *reinterpret_cast<const uint2*>(As + k * FW_LD + c);
    const float4 m4 = *reinterpret_cast<const float4*>(cm + c);
    const float a0 = bf_lo(u.x) - m4.x, a1 = bf_hi(u.x) - m4.y, a2 = bf_lo(u.y) - m4.z, a3 = bf_hi(u.y) - m4.w;
#pragma unroll
    for (int n = 0; n < 4; n++) {
      const float4 b = *reinterpret_cast<const float4*>(Bs + (nh + n) * 196 + c);
      acc[n] = fmaf(a0, b.x, acc[n]); acc[n] = fmaf(a1, b.y, acc[n]);
      acc[n] = fmaf(a2, b.z, acc[n]); acc[n] = fmaf(a3, b.w, acc[n]);
    }
  }
  const int p = k >> 6, kc = k & 63;
#pragma unroll
  for (int n = 0; n < 4; n++) {
    const int nn = n0 + nh + n;
    g_w[mat][p * (CH * 64) + nn * 64 + (((kc >> 3) ^ (nn & 7)) << 3) + (kc & 7)] = __float2bfloat16(acc[n]);
  }
}
constexpr int FW_SMEM = CH * FW_LD * 2 + (32 * CH + CH + 16 * 196) * 4;

struct Params {
  int role;
};

__device__ __forceinline__ uint32_t frag_addr(uint32_t slot_rowoff, uint32_t sw, int hiblk, int kk) {
  const int ci = 2 * kk + hiblk;
  return slot_rowoff + (ci >> 3) * PANEL_X + ((((uint32_t)ci & 7u) ^ sw) << 4);
}

__device__ __forceinline__ float row_rstd(uint32_t slot, int w, int lane) {
  const int row = 16 * w + (lane >> 1), half = lane & 1;
  const uint32_t rbase = slot + row * 128, sw = row & 7;
  float s0 = 0.f, s1 = 0.f, s2 = 0.f, s3 = 0.f, q0 = 0.f, q1 = 0.f, q2 = 0.f, q3 = 0.f;
#pragma unroll
  for (int i = 0; i < 12; i++) {
    const int c = half * 12 + i;
    const uint4 v = lds128(rbase + (c >> 3) * PANEL_X + ((((uint32_t)c & 7u) ^ sw) << 4));
    float lo, hi;
    lo = bf_lo(v.x); hi = bf_hi(v.x); s0 += lo; s1 += hi; q0 = fmaf(lo, lo, q0); q1 = fmaf(hi, hi, q1);
    lo = bf_lo(v.y); hi = bf_hi(v.y); s2 += lo; s3 += hi; q2 = fmaf(lo, lo, q2); q3 = fmaf(hi, hi, q3);
    lo = bf_lo(v.z); hi = bf_hi(v.z); s0 += lo; s1 += hi; q0 = fmaf(lo, lo, q0); q1 = fmaf(hi, hi, q1);
    lo = bf_lo(v.w); hi = bf_hi(v.w); s2 += lo; s3 += hi; q2 = fmaf(lo, lo, q2); q3 = fmaf(hi, hi, q3);
  }
  float s = (s0 + s1) + (s2 + s3), ss = (q0 + q1) + (q2 + q3);
  s += __shfl_xor_sync(0xffffffffu, s, 1);
  ss += __shfl_xor_sync(0xffffffffu, ss, 1);
  const float mean = s * (1.0f / CH);
  const float var = fmaxf(ss * (1.0f / CH) - mean * mean, 0.f);
  return rsqrtf(var + 1e-5f);
}

__global__ void __launch_bounds__(NWG * 128 + 128, 1)
swin_main_kernel(const __grid_constant__ CUtensorMap mapA_in, const __grid_constant__ CUtensorMap mapA_out,
                 const __grid_constant__ CUtensorMap mapB_in, const __grid_constant__ CUtensorMap mapB_out, const int num_a) {
  const int role = (int)blockIdx.x < num_a ? 0 : 1;
  const CUtensorMap* pmap_in = role == 0 ? &mapA_in : &mapB_in;
  const CUtensorMap* pmap_out = role == 0 ? &mapA_out : &mapB_out;
  extern __shared__ __align__(1024) uint8_t smem_raw[];
  const uint32_t sbase = smem_u32(smem_raw);
  const int tid = threadIdx.x, wg = tid >> 7, t128 = tid & 127, w = t128 >> 5, lane = tid & 31;
  const int g = lane >> 2, q = lane & 3;

  const uint32_t bar_w = sbase + SMEM_MISC;
  float* rbuf = reinterpret_cast<float*>(smem_raw + SMEM_RBUF) + wg * 64;

  if (tid == 0) {
    mbar_init(bar_w, 1);
    for (int i = 0; i < NSLOT; i++) { mbar_init(sbase + SMEM_MISC + 8 + 8 * i, 1); mbar_init(sbase + SMEM_MISC + 64 + 8 * i, 128); }
    asm volatile("fence.mbarrier_init.release.cluster;" ::: "memory");
  }
  for (int i = tid; i < NSLOT * SLOT_BYTES / 16; i += NWG * 128 + 128)
    *reinterpret_cast<uint4*>(smem_raw + SMEM_SLOT + i * 16) = make_uint4(0, 0, 0, 0);
  fence_proxy_async();
  __syncthreads();

  const int nunits = role == 0 ? NTILE_A : NUNIT_B;
  const int ustride = role == 0 ? num_a : (int)gridDim.x - num_a;
  const int ubase = role == 0 ? (int)blockIdx.x : (int)blockIdx.x - num_a;
  const int nj = (nunits - ubase + ustride - 1) / ustride;
  const uint32_t tx_bytes = role == 0 ? SLOT_BYTES : 3 * 49 * 128;

  auto coords = [&](int j, int& c1, int& c2, int& c3) {
    const int u = ubase + j * ustride;
    if (role == 0) { c1 = 0; c2 = (u % 14) * 16; c3 = u / 14; }
    else { const int t = u & 3, wx = (u >> 2) & 31, wy = u >> 7; c1 = wx * 7; c2 = wy * 7; c3 = t; }
  };
  auto issue_load = [&](int j) {
    int c1, c2, c3; coords(j, c1, c2, c3);
    if (role != 0) {
      const unsigned int* cnt = &g_band_cnt[c2 / 7];
      unsigned int v; int spins = 0;
      do {
        asm volatile("ld.acquire.gpu.global.u32 %0, [%1];" : "=r"(v) : "l"(cnt) : "memory");
        if (v >= 98u) break;
        __nanosleep(64);
      } while (++spins < (1 << 22));
      asm volatile("fence.proxy.async.global;" ::: "memory");
    }
    const int sl = j % NSLOT;
    const uint32_t bar = sbase + SMEM_MISC + 8 + 8 * sl;
    mbar_expect_tx(bar, tx_bytes);
#pragma unroll
    for (int p = 0; p < 3; p++) tma_load_4d(sbase + SMEM_SLOT + sl * SLOT_BYTES + p * PANEL_X, pmap_in, p * 64, c1, c2, c3, bar);
  };
  auto prefetch_l2 = [&](int j) {
    if (role == 0 && j < nj) {
      int c1, c2, c3; coords(j, c1, c2, c3);
#pragma unroll
      for (int p = 0; p < 3; p++) tma_prefetch_4d(pmap_in, p * 64, c1, c2, c3);
    }
  };

  if (tid >= NWG * 128) {
    asm volatile("setmaxnreg.dec.sync.aligned.u32 40;");
    if (tid == NWG * 128) {
      mbar_expect_tx(bar_w, 2 * WMAT_BYTES);
      bulk_load(sbase + SMEM_W0, &g_w[role * 2][0], WMAT_BYTES, bar_w);
      bulk_load(sbase + SMEM_W1, &g_w[role * 2 + 1][0], WMAT_BYTES, bar_w);
      for (int j = 0; j < NSLOT && j < nj; j++) issue_load(j);
      prefetch_l2(NSLOT); prefetch_l2(NSLOT + 1);
      for (int j = 0; j < nj; j++) {
        const int sl = j % NSLOT;
        mbar_wait(sbase + SMEM_MISC + 64 + 8 * sl, (j / NSLOT) & 1);
        int c1, c2, c3; coords(j, c1, c2, c3);
#pragma unroll
        for (int p = 0; p < 3; p++) tma_store_4d(pmap_out, sbase + SMEM_SLOT + sl * SLOT_BYTES + p * PANEL_X, p * 64, c1, c2, c3);
        bulk_commit();
        bulk_wait_read0();
        if (j + NSLOT < nj) issue_load(j + NSLOT);
        prefetch_l2(j + NSLOT + 2);
        if (role == 0) {
          bulk_wait0();
          asm volatile("fence.proxy.async.global;" ::: "memory");
          __threadfence();
          atomicAdd(&g_band_cnt[c3 / 7], 1u);
        }
      }
      bulk_wait0();
    }
    return;
  }
  asm volatile("setmaxnreg.inc.sync.aligned.u32 232;");
  mbar_wait(bar_w, 0);

  const int blk = lane >> 3;
  const int frow = 16 * w + (lane & 7) + ((blk & 1) << 3);
  const uint32_t fsw = frow & 7;
  const int fhi = blk >> 1;

  const uint64_t dW0 = make_desc(sbase + SMEM_W0, 16, 1024);
  const uint64_t dW1 = make_desc(sbase + SMEM_W1, 16, 1024);

  const float scale_l2e = 0.07216878364870322f * 1.4426950408889634f;

  for (int j = wg; j < nj; j += NWG) {
    const int sl = j % NSLOT;
    const uint32_t slot = sbase + SMEM_SLOT + sl * SLOT_BYTES;
    const uint32_t frowoff = slot + frow * 128;
    const uint64_t dX = make_desc(slot, 16, 1024);
    const uint64_t dXmn = make_desc(slot, PANEL_X, 1024);
    PH(0);
    mbar_wait(sbase + SMEM_MISC + 8 + 8 * sl, (j / NSLOT) & 1);
    PH(1);

    float acc[96];
    wgmma_fence();
#pragma unroll
    for (int kk = 0; kk < 12; kk++) {
      const uint32_t off = (kk >> 2) * PANEL_X + (kk & 3) * 32;
      const uint32_t offw = (kk >> 2) * PANEL_W + (kk & 3) * 32;
      wgmma_n192_ss(acc, dX + (off >> 4), dW0 + (offw >> 4), kk);
    }
    wgmma_commit();
    PH(2);
    const float rmine = row_rstd(slot, w, lane);
    PH(3);
    uint32_t fr[48], xf[48];

    if (role == 0) {
      wgmma_wait0(); acc_fence(acc);
      PH(4);
#pragma unroll
      for (int i = 0; i < 48; i++) fr[i] = pack_bf16(acc[2 * i], acc[2 * i + 1]);
#pragma unroll
      for (int kk = 0; kk < 12; kk++) ldsm_x4(frag_addr(frowoff, fsw, fhi, kk), xf[4 * kk], xf[4 * kk + 1], xf[4 * kk + 2], xf[4 * kk + 3]);
#pragma unroll
      for (int kk = 0; kk < 12; kk++) {
#pragma unroll
        for (int i = 0; i < 8; i++) acc[8 * kk + i] = 0.f;
        mma_16816(acc[8 * kk + 0], acc[8 * kk + 1], acc[8 * kk + 2], acc[8 * kk + 3], fr[4 * kk], fr[4 * kk + 1], fr[4 * kk + 2], fr[4 * kk + 3], xf[4 * kk], xf[4 * kk + 2]);
        mma_16816(acc[8 * kk + 4], acc[8 * kk + 5], acc[8 * kk + 6], acc[8 * kk + 7], fr[4 * kk], fr[4 * kk + 1], fr[4 * kk + 2], fr[4 * kk + 3], xf[4 * kk + 1], xf[4 * kk + 3]);
      }
      float d0[4], d1[4];
      {
        float t0 = 0.f, t1 = 0.f, t2 = 0.f, t3 = 0.f, u0 = 0.f, u1 = 0.f, u2 = 0.f, u3 = 0.f;
#pragma unroll
        for (int kk = 0; kk < 12; kk += 2) {
          t0 += acc[8 * kk + 0]; t1 += acc[8 * kk + 1]; t2 += acc[8 * kk + 6]; t3 += acc[8 * kk + 7];
          u0 += acc[8 * kk + 8]; u1 += acc[8 * kk + 9]; u2 += acc[8 * kk + 14]; u3 += acc[8 * kk + 15];
        }
        d0[0] = t0 + u0; d0[1] = t1 + u1; d1[2] = t2 + u2; d1[3] = t3 + u3;
      }
      const float rA = __shfl_sync(0xffffffffu, rmine, 2 * g);
      const float rB = __shfl_sync(0xffffffffu, rmine, 2 * g + 16);
      const float k0 = __shfl_sync(0xffffffffu, rmine, 4 * q);
      const float k1 = __shfl_sync(0xffffffffu, rmine, 4 * q + 2);
      const float k2 = __shfl_sync(0xffffffffu, rmine, 4 * q + 16);
      const float k3 = __shfl_sync(0xffffffffu, rmine, 4 * q + 18);
      const bool valid = (g >> 2) == (q >> 1);
      float sa0 = d0[0] * k0 * (rA * scale_l2e), sa1 = d0[1] * k1 * (rA * scale_l2e);
      float sb0 = d1[2] * k2 * (rB * scale_l2e), sb1 = d1[3] * k3 * (rB * scale_l2e);
      float ma = fmaxf(sa0, sa1), mb = fmaxf(sb0, sb1);
      ma = fmaxf(ma, __shfl_xor_sync(0xffffffffu, ma, 1));
      mb = fmaxf(mb, __shfl_xor_sync(0xffffffffu, mb, 1));
      const float ea0 = exp2f(sa0 - ma), ea1 = exp2f(sa1 - ma);
      const float eb0 = exp2f(sb0 - mb), eb1 = exp2f(sb1 - mb);
      float suma = ea0 + ea1, sumb = eb0 + eb1;
      suma += __shfl_xor_sync(0xffffffffu, suma, 1);
      sumb += __shfl_xor_sync(0xffffffffu, sumb, 1);
      const float ia = __fdividef(1.f, suma), ib = __fdividef(1.f, sumb);
      const uint32_t pa0 = valid ? pack_bf16(ea0 * ia * k0, ea1 * ia * k1) : 0u;
      const uint32_t pa3 = valid ? pack_bf16(eb0 * ib * k2, eb1 * ib * k3) : 0u;
      PH(5);
#pragma unroll
      for (int hh = 0; hh < 2; hh++) {
        uint32_t bt[24];
#pragma unroll
        for (int jj = 0; jj < 6; jj++) ldsm_x4_t(frag_addr(frowoff, fsw, fhi, hh * 6 + jj), bt[4 * jj], bt[4 * jj + 1], bt[4 * jj + 2], bt[4 * jj + 3]);
#pragma unroll
        for (int jj = 0; jj < 6; jj++) {
          const int o = 8 * (hh * 6 + jj);
          acc[o + 0] = 0.f; acc[o + 1] = 0.f; acc[o + 2] = 0.f; acc[o + 3] = 0.f;
          acc[o + 4] = 0.f; acc[o + 5] = 0.f; acc[o + 6] = 0.f; acc[o + 7] = 0.f;
          mma_16816(acc[o + 0], acc[o + 1], acc[o + 2], acc[o + 3], pa0, 0u, 0u, pa3, bt[4 * jj], bt[4 * jj + 1]);
          mma_16816(acc[o + 4], acc[o + 5], acc[o + 6], acc[o + 7], pa0, 0u, 0u, pa3, bt[4 * jj + 2], bt[4 * jj + 3]);
        }
      }
    } else {
      if ((lane & 1) == 0) rbuf[16 * w + (lane >> 1)] = rmine;
      wg_bar(1 + wg);
      wgmma_wait0(); acc_fence(acc);
      PH(4);
#pragma unroll
      for (int i = 0; i < 48; i++) fr[i] = pack_bf16(acc[2 * i], acc[2 * i + 1]);
      float s[28], s2[28];
      wgmma_fence();
#pragma unroll
      for (int kk = 0; kk < 12; kk += 2) {
        const uint32_t off = (kk >> 2) * PANEL_X + (kk & 3) * 32;
        wgmma_n56_rs(s, fr[4 * kk], fr[4 * kk + 1], fr[4 * kk + 2], fr[4 * kk + 3], dX + (off >> 4), kk);
        wgmma_n56_rs(s2, fr[4 * kk + 4], fr[4 * kk + 5], fr[4 * kk + 6], fr[4 * kk + 7], dX + ((off + 32) >> 4), kk);
      }
      wgmma_commit();
      float rj[14];
#pragma unroll
      for (int j = 0; j < 7; j++) {
        const float2 v = *reinterpret_cast<const float2*>(&rbuf[8 * j + 2 * q]);
        rj[2 * j] = v.x; rj[2 * j + 1] = v.y;
      }
      const float ri0 = rbuf[16 * w + g] * scale_l2e, ri1 = rbuf[16 * w + g + 8] * scale_l2e;
      wgmma_wait0(); acc_fence(s); acc_fence(s2);
#pragma unroll
      for (int i = 0; i < 28; i++) s[i] += s2[i];
      PH(5);
      float m0 = -INFINITY, m1 = -INFINITY;
#pragma unroll
      for (int j = 0; j < 7; j++) {
#pragma unroll
        for (int e = 0; e < 2; e++) {
          const bool ok = (j < 6) || (2 * q + e == 0);
          float v0 = s[4 * j + e] * rj[2 * j + e] * ri0;
          float v1 = s[4 * j + 2 + e] * rj[2 * j + e] * ri1;
          v0 = ok ? v0 : -INFINITY; v1 = ok ? v1 : -INFINITY;
          s[4 * j + e] = v0; s[4 * j + 2 + e] = v1;
          m0 = fmaxf(m0, v0); m1 = fmaxf(m1, v1);
        }
      }
      m0 = fmaxf(m0, __shfl_xor_sync(0xffffffffu, m0, 1)); m0 = fmaxf(m0, __shfl_xor_sync(0xffffffffu, m0, 2));
      m1 = fmaxf(m1, __shfl_xor_sync(0xffffffffu, m1, 1)); m1 = fmaxf(m1, __shfl_xor_sync(0xffffffffu, m1, 2));
      float sum0 = 0.f, sum1 = 0.f;
#pragma unroll
      for (int j = 0; j < 7; j++) {
#pragma unroll
        for (int e = 0; e < 2; e++) {
          const float e0 = exp2f(s[4 * j + e] - m0), e1 = exp2f(s[4 * j + 2 + e] - m1);
          s[4 * j + e] = e0; s[4 * j + 2 + e] = e1;
          sum0 += e0; sum1 += e1;
        }
      }
      sum0 += __shfl_xor_sync(0xffffffffu, sum0, 1); sum0 += __shfl_xor_sync(0xffffffffu, sum0, 2);
      sum1 += __shfl_xor_sync(0xffffffffu, sum1, 1); sum1 += __shfl_xor_sync(0xffffffffu, sum1, 2);
      const float i0 = __fdividef(1.f, sum0), i1 = __fdividef(1.f, sum1);
      uint32_t pa[16];
#pragma unroll
      for (int j = 0; j < 7; j++) {
        pa[(j >> 1) * 4 + (j & 1) * 2 + 0] = pack_bf16(s[4 * j] * i0 * rj[2 * j], s[4 * j + 1] * i0 * rj[2 * j + 1]);
        pa[(j >> 1) * 4 + (j & 1) * 2 + 1] = pack_bf16(s[4 * j + 2] * i1 * rj[2 * j], s[4 * j + 3] * i1 * rj[2 * j + 1]);
      }
      pa[14] = 0u; pa[15] = 0u;
      PH(6);
      wgmma_fence();
#pragma unroll
      for (int kk = 0; kk < 4; kk++)
        wgmma_n192_rs_tb(acc, pa[4 * kk], pa[4 * kk + 1], pa[4 * kk + 2], pa[4 * kk + 3], dXmn + ((kk * 2048) >> 4), kk);
      wgmma_commit();
      wgmma_wait0(); acc_fence(acc);
    }

    PH(7);
#pragma unroll
    for (int i = 0; i < 48; i++) fr[i] = pack_bf16(acc[2 * i], acc[2 * i + 1]);
    wgmma_fence();
#pragma unroll
    for (int kk = 0; kk < 12; kk++) {
      const uint32_t offw = (kk >> 2) * PANEL_W + (kk & 3) * 32;
      wgmma_n192_rs(acc, fr[4 * kk], fr[4 * kk + 1], fr[4 * kk + 2], fr[4 * kk + 3], dW1 + (offw >> 4), kk);
    }
    wgmma_commit();
    if (role != 0) {
#pragma unroll
      for (int kk = 0; kk < 12; kk++) ldsm_x4(frag_addr(frowoff, fsw, fhi, kk), xf[4 * kk], xf[4 * kk + 1], xf[4 * kk + 2], xf[4 * kk + 3]);
    }
    wgmma_wait0(); acc_fence(acc);
    PH(8);
    wg_bar(1 + wg);
    PH(9);
#pragma unroll
    for (int kk = 0; kk < 12; kk++) {
      const uint32_t o0 = add_bf16x2(xf[4 * kk + 0], pack_bf16(acc[8 * kk + 0], acc[8 * kk + 1]));
      const uint32_t o1 = add_bf16x2(xf[4 * kk + 1], pack_bf16(acc[8 * kk + 2], acc[8 * kk + 3]));
      const uint32_t o2 = add_bf16x2(xf[4 * kk + 2], pack_bf16(acc[8 * kk + 4], acc[8 * kk + 5]));
      const uint32_t o3 = add_bf16x2(xf[4 * kk + 3], pack_bf16(acc[8 * kk + 6], acc[8 * kk + 7]));
      stsm_x4(frag_addr(frowoff, fsw, fhi, kk), o0, o1, o2, o3);
    }
    PH(10);
    fence_proxy_async();
    mbar_arrive(sbase + SMEM_MISC + 64 + 8 * sl);
    PH(11);
  }
}

typedef CUresult (*EncodeTiledFn)(CUtensorMap*, CUtensorMapDataType, cuuint32_t, void*, const cuuint64_t*, const cuuint64_t*,
                                  const cuuint32_t*, const cuuint32_t*, CUtensorMapInterleave, CUtensorMapSwizzle,
                                  CUtensorMapL2promotion, CUtensorMapFloatOOBfill);

bool make_map(EncodeTiledFn fn, CUtensorMap* m, void* base, bool pixel_major) {
  cuuint64_t dims[4]; cuuint64_t strides[3]; cuuint32_t box[4]; cuuint32_t es[4] = {1, 1, 1, 1};
  const cuuint64_t sC = (cuuint64_t)CH * 2, sW = sC * WW, sT = sW * HH;
  if (pixel_major) {
    dims[0] = CH; dims[1] = TT; dims[2] = WW; dims[3] = HH;
    strides[0] = sT; strides[1] = sC; strides[2] = sW;
    box[0] = 64; box[1] = 4; box[2] = 16; box[3] = 1;
  } else {
    dims[0] = CH; dims[1] = WW; dims[2] = HH; dims[3] = TT;
    strides[0] = sC; strides[1] = sW; strides[2] = sT;
    box[0] = 64; box[1] = 7; box[2] = 7; box[3] = 1;
  }
  return fn(m, CU_TENSOR_MAP_DATA_TYPE_BFLOAT16, 4, base, dims, strides, box, es, CU_TENSOR_MAP_INTERLEAVE_NONE,
            CU_TENSOR_MAP_SWIZZLE_128B, CU_TENSOR_MAP_L2_PROMOTION_L2_256B, CU_TENSOR_MAP_FLOAT_OOB_FILL_NONE) == CUDA_SUCCESS;
}

}

extern "C" void kernel_launch(void* const* d_in, const int* in_sizes, int n_in, void* d_out, int out_size) {
  const __nv_bfloat16* x = (const __nv_bfloat16*)d_in[0];
  const __nv_bfloat16* wqkv_t = (const __nv_bfloat16*)d_in[1];
  const __nv_bfloat16* wo_t = (const __nv_bfloat16*)d_in[2];
  const __nv_bfloat16* wqkv_s = (const __nv_bfloat16*)d_in[3];
  const __nv_bfloat16* wo_s = (const __nv_bfloat16*)d_in[4];

  static bool init = false;
  static CUtensorMap mA_in, mA_out, mB_in, mB_out;
  static void* last_x = nullptr; static void* last_out = nullptr;
  static int nsm = 132;
  if (!init || last_x != d_in[0] || last_out != d_out) {
    void* fnp = nullptr; cudaDriverEntryPointQueryResult qr;
    cudaGetDriverEntryPoint("cuTensorMapEncodeTiled", &fnp, cudaEnableDefault, &qr);
    EncodeTiledFn fn = (EncodeTiledFn)fnp;
    void* x1p = nullptr; cudaGetSymbolAddress(&x1p, g_x1);
    make_map(fn, &mA_in, (void*)x, true);
    make_map(fn, &mA_out, x1p, true);
    make_map(fn, &mB_in, x1p, false);
    make_map(fn, &mB_out, d_out, false);
    cudaFuncSetAttribute(fold_weights_kernel, cudaFuncAttributeMaxDynamicSharedMemorySize, FW_SMEM);
    cudaFuncSetAttribute(swin_main_kernel, cudaFuncAttributeMaxDynamicSharedMemorySize, SMEM_TOTAL);
    cudaDeviceGetAttribute(&nsm, cudaDevAttrMultiProcessorCount, 0);
    init = true; last_x = d_in[0]; last_out = d_out;
  }
  fold_weights_kernel<<<dim3(24, 4), 384, FW_SMEM>>>(wqkv_t, wo_t, wqkv_s, wo_s);
  swin_main_kernel<<<nsm, NWG * 128 + 128, SMEM_TOTAL>>>(mA_in, mA_out, mB_in, mB_out, NUM_A);
}
```
